```python
import torch

def _softmax(x, axis=-1):
    return torch.softmax(x, dim=axis)
def _gelu(x):
    return torch.nn.functional.gelu(x, approximate="tanh")
def _silu(x):
    return torch.nn.functional.silu(x)
def _sigmoid(x):
    return torch.sigmoid(x)
def _layernorm(x, axis=-1, eps=1e-5):
    m = x.mean(dim=axis, keepdim=True)
    v = x.var(dim=axis, keepdim=True, unbiased=False)
    return (x - m) / torch.sqrt(v + eps)
def _scatter_add(tgt, idx, src, axis=0):
    return tgt.clone().index_add_(axis, idx, src)
def _segment_sum(src, seg, n):
    out = torch.zeros((n,) + src.shape[1:], dtype=src.dtype)
    return out.index_add_(0, seg, src)
def _pad(x, pw):
    flat = tuple(v for pair in reversed(pw) for v in pair)
    return torch.nn.functional.pad(x, flat)

kernel_name = 'interleave_layers__linear_attn_block__dense_activation_gelu__prompt'

def setup_inputs():

    _w = (lambda a: (lambda t: t.to(torch.bfloat16) if t.is_floating_point() else t)(torch.as_tensor(a)))
    def _A_setup():
        B, S, D = 1, 2048, 512
        return {
            "x": _w((lambda *s: torch.randn(*s, dtype=torch.bfloat16) * 0.05)(B, S, D)),
            "wqkv": _w((lambda *s: torch.randn(*s, dtype=torch.bfloat16) * 0.05)(D, 3 * D)),
            "wo": _w((lambda *s: torch.randn(*s, dtype=torch.bfloat16) * 0.05)(D, D)),
        }
    _A_in = _A_setup()

    def _B_setup():
        B, S, D, F = 1, 2048, 512, 1792
        return {
            "x": _w((lambda *s: torch.randn(*s, dtype=torch.bfloat16) * 0.05)(B, S, D)),
            "w1": _w((lambda *s: torch.randn(*s, dtype=torch.bfloat16) * 0.8)(D, F) * (D ** -0.5)),
            "b1": _w((lambda *s: torch.randn(*s, dtype=torch.bfloat16) * 0.8)(F) * 0.01),
            "w2": _w((lambda *s: torch.randn(*s, dtype=torch.bfloat16) * 0.8)(F, D) * (F ** -0.5)),
            "b2": _w((lambda *s: torch.randn(*s, dtype=torch.bfloat16) * 0.8)(D) * 0.01),
        }
    _B_in = _B_setup()

    return {
        "A_x": _A_in["x"],
        "A_wqkv": _A_in["wqkv"],
        "A_wo": _A_in["wo"],
        "B_x": _B_in["x"],
        "B_w1": _B_in["w1"],
        "B_b1": _B_in["b1"],
        "B_w2": _B_in["w2"],
        "B_b2": _B_in["b2"],
    }

def reference(A_x, A_wqkv, A_wo, B_x, B_w1, B_b1, B_w2, B_b2):
    def _A_ref(x, wqkv, wo):
        B, S, D = x.shape
        H = 32; Dh = D // H
        qkv = (lambda x, *d: x.permute(*d))((x @ wqkv).reshape(B, S, 3, H, Dh), 2, 0, 3, 1, 4)
        q, k, v = qkv[0], qkv[1], qkv[2]
        phi = lambda t: torch.where(t > 0, t + 1, torch.exp(t)) + 1e-6
        pq, pk = phi(q), phi(k)
        kv = torch.einsum("bhsd,bhse->bhde", pk, v)
        z = torch.einsum("bhsd->bhd", pk)
        num = torch.einsum("bhqd,bhde->bhqe", pq, kv)
        den = torch.einsum("bhqd,bhd->bhq", pq, z)[..., None] + 1e-6
        o = num / den
        return (lambda x, *d: x.permute(*d))(o, 0, 2, 1, 3).reshape(B, S, D) @ wo

    def _B_ref(x, w1, b1, w2, b2):
        h = torch.einsum("bsd,df->bsf", x, w1) + b1
        h = _gelu(h)
        return torch.einsum("bsf,fd->bsd", h, w2) + b2

    x = A_x
    x = x + _A_ref(_layernorm(x, axis=-1), A_wqkv, A_wo)
    x = x + _B_ref(_layernorm(x, axis=-1), B_w1, B_b1, B_w2, B_b2)
    x = x + _A_ref(_layernorm(x, axis=-1), A_wqkv, A_wo)
    x = x + _B_ref(_layernorm(x, axis=-1), B_w1, B_b1, B_w2, B_b2)
    return x
```

```cpp
#include <cuda_runtime.h>
#include <cuda_bf16.h>
#include <cuda.h>
#include <stdint.h>

#define GT 7
#define PROW EX_X
#define MAPG 2
#define SAME 1
#define PQ 2
#define D_O 1000
#define D_X 0
#define NLAYER 2
#define CREGS "240"
#define HREGS "24"
#define NQ 1
#define PRIO_MASK 0
#define PRIO_AT 4
#define LAG 4
#define LAGP 2

namespace {

constexpr int NGRP = 16;
constexpr int NS = 5;
constexpr int CH = 16384;

constexpr int OFF_B = 0;
constexpr int OFF_W = NS * 2 * CH;
constexpr int OFF_KT = OFF_W;
constexpr int OFF_VT = OFF_W + CH;
constexpr int OFF_ONE = OFF_W + 2 * CH;
constexpr int OFF_TB = OFF_W + 3 * CH;
constexpr int OFF_B1 = OFF_W + 4 * CH;
constexpr int OFF_BAR = OFF_B1 + 1792;
constexpr int BAR_BFULL = 0;
constexpr int BAR_BEMPTY = BAR_BFULL + NS;
constexpr int BAR_WFULL = BAR_BEMPTY + NS;
constexpr int BAR_Z = BAR_WFULL + 22;
constexpr int NBAR = BAR_Z + 2;
constexpr int SMEM_BYTES = OFF_BAR + NBAR * 8;
static_assert(SMEM_BYTES <= 232448, "smem");

constexpr int EX_O = 0, EX_X1 = 8, EX_X = 16;
constexpr int EX_P = 24;
constexpr int ROW = 1032;
__device__ __align__(1024) uint4 g_ex[NGRP][88][ROW];
__device__ __align__(1024) uint4 g_st[2][NGRP][8][64];
__device__ __align__(1024) uint4 g_kvp[8][NGRP][128];
__device__ __align__(1024) uint4 g_kvz[8][NGRP][16];
#define PROBE(k) do { } while (0)
#define PROBE_DECL
#define PROBE_OUT(a, n) do { } while (0)
#define TS(role, id) do { } while (0)
#define RETRY(k) do { } while (0)

__device__ __forceinline__ uint32_t smem_u32(const void* p) { return (uint32_t)__cvta_generic_to_shared(p); }
__device__ __forceinline__ void mbar_init(uint32_t a, uint32_t c) { asm volatile("mbarrier.init.shared::cta.b64 [%0], %1;" ::"r"(a), "r"(c) : "memory"); }
__device__ __forceinline__ void mbar_expect_tx(uint32_t a, uint32_t b) { asm volatile("mbarrier.arrive.expect_tx.shared::cta.b64 _, [%0], %1;" ::"r"(a), "r"(b) : "memory"); }
__device__ __forceinline__ void mbar_arrive(uint32_t a) { asm volatile("mbarrier.arrive.shared::cta.b64 _, [%0];" ::"r"(a) : "memory"); }
#define SPIN_LIMIT "262144"
__device__ __forceinline__ void mbar_wait(uint32_t a, uint32_t p, uint32_t& n) {
  asm volatile("{\n.reg .pred p, q;\nLAB_WAIT:\nmbarrier.try_wait.parity.shared::cta.b64 p, [%1], %2;\n"
               "add.u32 %0, %0, 1;\nsetp.lt.and.u32 q, %0, " SPIN_LIMIT ", !p;\n@q bra LAB_WAIT;\n}"
               : "+r"(n) : "r"(a), "r"(p) : "memory");
}
__device__ __forceinline__ bool again(uint32_t t, uint32_t& n) {
  uint32_t r;
  asm volatile("{\n.reg .pred p;\n.reg .b32 t;\nand.b32 t, %2, 1;\nsetp.ne.u32 p, t, 0;\nvote.sync.any.pred p, p, 0xffffffff;\n"
               "add.u32 %1, %1, 16;\nsetp.lt.and.u32 p, %1, " SPIN_LIMIT ", p;\nselp.u32 %0, 1, 0, p;\n}"
               : "=r"(r), "+r"(n) : "r"(t) : "memory");
  return r;
}
__device__ __forceinline__ uint32_t differ(uint32_t a, uint32_t b, uint32_t m) { uint32_t d; asm("lop3.b32 %0, %1, %2, %3, 0x7e;" : "=r"(d) : "r"(a), "r"(b), "r"(m)); return d; }
__device__ __forceinline__ bool elect_one() {
  uint32_t p;
  asm volatile("{\n.reg .pred P;\nelect.sync _|P, 0xffffffff;\nselp.u32 %0, 1, 0, P;\n}" : "=r"(p));
  return p;
}
__device__ __forceinline__ void tma_load2d(uint32_t dst, const CUtensorMap* m, int c0, int c1, uint32_t bar) {
  asm volatile("cp.async.bulk.tensor.2d.shared::cluster.global.mbarrier::complete_tx::bytes [%0], [%1, {%3, %4}], [%2];"
               ::"r"(dst), "l"(m), "r"(bar), "r"(c0), "r"(c1) : "memory");
}
__device__ __forceinline__ void tma_load2d_both(uint32_t dst, const CUtensorMap* m, int c0, int c1, uint32_t bar) {
  asm volatile("cp.async.bulk.tensor.2d.shared::cluster.global.mbarrier::complete_tx::bytes.multicast::cluster [%0], [%1, {%3, %4}], [%2], %5;"
               ::"r"(dst), "l"(m), "r"(bar), "r"(c0), "r"(c1), "h"((uint16_t)3) : "memory");
}
__device__ __forceinline__ void tma_store2d(const CUtensorMap* m, int c0, int c1, uint32_t src) {
  asm volatile("cp.async.bulk.tensor.2d.global.shared::cta.bulk_group [%0, {%2, %3}], [%1];" ::"l"(m), "r"(src), "r"(c0), "r"(c1) : "memory");
}
__device__ __forceinline__ void bulk_load(uint32_t dst, const void* src, uint32_t bytes, uint32_t bar) {
  asm volatile("cp.async.bulk.shared::cluster.global.mbarrier::complete_tx::bytes [%0], [%1], %2, [%3];" ::"r"(dst), "l"(src), "r"(bytes), "r"(bar) : "memory");
}
__device__ __forceinline__ void bulk_prefetch_l2(const void* src, uint32_t bytes) {
  asm volatile("cp.async.bulk.prefetch.L2.global [%0], %1;" ::"l"(src), "r"(bytes) : "memory");
}
__device__ __forceinline__ void fence_init() { asm volatile("fence.mbarrier_init.release.cluster;\nfence.proxy.async.shared::cta;" ::: "memory"); }
__device__ __forceinline__ void fence_async_smem() { asm volatile("fence.proxy.async.shared::cta;" ::: "memory"); }
__device__ __forceinline__ void bar_sync(int id, int n) { asm volatile("bar.sync %0, %1;" ::"r"(id), "r"(n) : "memory"); }
__device__ __forceinline__ uint32_t ld_relaxed(const uint32_t* p) { uint32_t v; asm volatile("ld.relaxed.gpu.global.u32 %0, [%1];" : "=r"(v) : "l"(p) : "memory"); return v; }
__device__ __forceinline__ void st_b128(void* p, uint32_t a, uint32_t b, uint32_t c, uint32_t d) {
  asm volatile("{\n.reg .b64 lo, hi;\n.reg .b128 t;\nmov.b64 lo, {%1, %2};\nmov.b64 hi, {%3, %4};\nmov.b128 t, {lo, hi};\nst.relaxed.gpu.global.b128 [%0], t;\n}"
               ::"l"(p), "r"(a), "r"(b), "r"(c), "r"(d) : "memory");
}
__device__ __forceinline__ void ld_b128(const void* p, uint32_t& a, uint32_t& b, uint32_t& c, uint32_t& d) {
  asm volatile("{\n.reg .b64 lo, hi;\n.reg .b128 t;\nld.relaxed.gpu.global.b128 t, [%4];\nmov.b128 {lo, hi}, t;\nmov.b64 {%0, %1}, lo;\nmov.b64 {%2, %3}, hi;\n}"
               : "=r"(a), "=r"(b), "=r"(c), "=r"(d) : "l"(p) : "memory");
}
__device__ __forceinline__ float4 lds_f4(uint32_t a) { float4 v; asm volatile("ld.shared.v4.f32 {%0, %1, %2, %3}, [%4];" : "=f"(v.x), "=f"(v.y), "=f"(v.z), "=f"(v.w) : "r"(a)); return v; }
__device__ __forceinline__ float2 lds_f2(uint32_t a) { float2 v; asm volatile("ld.shared.v2.f32 {%0, %1}, [%2];" : "=f"(v.x), "=f"(v.y) : "r"(a)); return v; }
__device__ __forceinline__ void stsm4(uint32_t a, uint32_t r0, uint32_t r1, uint32_t r2, uint32_t r3) {
  asm volatile("stmatrix.sync.aligned.m8n8.x4.shared.b16 [%0], {%1, %2, %3, %4};" ::"r"(a), "r"(r0), "r"(r1), "r"(r2), "r"(r3) : "memory");
}
__device__ __forceinline__ void ldsm4(uint32_t a, uint32_t& r0, uint32_t& r1, uint32_t& r2, uint32_t& r3) {
  asm volatile("ldmatrix.sync.aligned.m8n8.x4.shared.b16 {%0, %1, %2, %3}, [%4];" : "=r"(r0), "=r"(r1), "=r"(r2), "=r"(r3) : "r"(a) : "memory");
}
__device__ __forceinline__ uint32_t pack_bf16(float lo, float hi) { uint32_t d; asm("cvt.rn.bf16x2.f32 %0, %1, %2;" : "=r"(d) : "f"(hi), "f"(lo)); return d; }
__device__ __forceinline__ float bf_lo(uint32_t w) { return __uint_as_float(w << 16); }
__device__ __forceinline__ float bf_hi(uint32_t w) { return __uint_as_float(w & 0xffff0000u); }
__device__ __forceinline__ void mma16816(float (&c)[4], uint32_t a0, uint32_t a1, uint32_t a2, uint32_t a3, uint32_t b0, uint32_t b1) {
  asm volatile("mma.sync.aligned.m16n8k16.row.col.f32.bf16.bf16.f32 {%0, %1, %2, %3}, {%4, %5, %6, %7}, {%8, %9}, {%0, %1, %2, %3};"
               : "+f"(c[0]), "+f"(c[1]), "+f"(c[2]), "+f"(c[3]) : "r"(a0), "r"(a1), "r"(a2), "r"(a3), "r"(b0), "r"(b1));
}
__device__ __forceinline__ float ex2(float x) { float y; asm("ex2.approx.ftz.f32 %0, %1;" : "=f"(y) : "f"(x)); return y; }
__device__ __forceinline__ float tanh_fast(float x) { float y; asm("tanh.approx.f32 %0, %1;" : "=f"(y) : "f"(x)); return y; }
__device__ __forceinline__ float rcp_fast(float x) { float y; asm("rcp.approx.ftz.f32 %0, %1;" : "=f"(y) : "f"(x)); return y; }
__device__ __forceinline__ uint32_t phi2(float t0, float t1) {
  const uint32_t tt = pack_bf16(t0, t1), ee = pack_bf16(ex2(t0 * 1.4426950408889634f), ex2(t1 * 1.4426950408889634f));
  uint32_t d;
  asm("{\n.reg .b32 x, y;\nmax.bf16x2 x, %1, %3;\nmin.bf16x2 y, %2, %4;\nadd.rn.bf16x2 %0, x, y;\n}"
      : "=r"(d) : "r"(tt), "r"(ee), "r"(0x35863586u), "r"(0x3f803f80u));
  return d;
}
__device__ __forceinline__ uint32_t fma_bf16x2(uint32_t a, uint32_t b, uint32_t c) { uint32_t d; asm("fma.rn.bf16x2 %0, %1, %2, %3;" : "=r"(d) : "r"(a), "r"(b), "r"(c)); return d; }
__device__ __forceinline__ uint32_t lds_u1(uint32_t a) { uint32_t v; asm volatile("ld.shared.b32 %0, [%1];" : "=r"(v) : "r"(a)); return v; }
__device__ __forceinline__ void sts_u1(uint32_t a, uint32_t x) { asm volatile("st.shared.b32 [%0], %1;" ::"r"(a), "r"(x) : "memory"); }
__device__ __forceinline__ void bar_arrive(int id, int n) { asm volatile("bar.arrive %0, %1;" ::"r"(id), "r"(n) : "memory"); }
__device__ __forceinline__ void sts_u2(uint32_t a, uint32_t x, uint32_t y) { asm volatile("st.shared.v2.b32 [%0], {%1, %2};" ::"r"(a), "r"(x), "r"(y) : "memory"); }
__device__ __forceinline__ void sts_u4(uint32_t a, uint32_t x, uint32_t y, uint32_t z, uint32_t w) { asm volatile("st.shared.v4.b32 [%0], {%1, %2, %3, %4};" ::"r"(a), "r"(x), "r"(y), "r"(z), "r"(w) : "memory"); }
__device__ __forceinline__ void lds_u4(uint32_t a, uint32_t& x, uint32_t& y, uint32_t& z, uint32_t& w) { asm volatile("ld.shared.v4.b32 {%0, %1, %2, %3}, [%4];" : "=r"(x), "=r"(y), "=r"(z), "=r"(w) : "r"(a) : "memory"); }
__device__ __forceinline__ float gelu_half(float y) {
  const float u = y * fmaf(y * y, 8.f * 0.7978845608028654f * 0.044715f, 2.f * 0.7978845608028654f);
  return fmaf(y, tanh_fast(u), y);
}
__device__ __forceinline__ void wg_fence() { asm volatile("wgmma.fence.sync.aligned;" ::: "memory"); }
__device__ __forceinline__ void wg_commit() { asm volatile("wgmma.commit_group.sync.aligned;" ::: "memory"); }
template <int N> __device__ __forceinline__ void wg_wait() { asm volatile("wgmma.wait_group.sync.aligned %0;" ::"n"(N) : "memory"); }
template <int N> __device__ __forceinline__ void fence_regs(float (&d)[N]) {
#pragma unroll
  for (int i = 0; i < N; i++) asm volatile("" : "+f"(d[i])::"memory");
}
template <int N> __device__ __forceinline__ void zero_regs(float (&d)[N]) {
#pragma unroll
  for (int i = 0; i < N; i += 2) asm volatile("mov.b64 {%0, %1}, 0;" : "=f"(d[i]), "=f"(d[i + 1])::"memory");
}
__device__ __forceinline__ uint32_t mk_desc(uint32_t addr) { return ((addr & 0x3FFFF) >> 4) | ((8192 >> 4) << 16); }
__device__ __forceinline__ void fence_gpu() { asm volatile("fence.acq_rel.gpu;" ::: "memory"); }

__device__ __forceinline__ void wgmma_rs_acc(float (&d)[112], uint32_t a0, uint32_t a1, uint32_t a2, uint32_t a3, uint32_t db) {
  asm volatile("{\n.reg .pred p;\n.reg .b64 db;\nsetp.ne.b32 p, 1, 0;\nmov.b64 db, {%116, 1073741888};\n"
    "wgmma.mma_async.sync.aligned.m64n224k16.f32.bf16.bf16 {%0, %1, %2, %3, %4, %5, %6, %7, %8, %9, %10, %11, %12, %13, %14, %15, %16, %17, %18, %19, %20, %21, %22, %23, %24, %25, %26, %27, %28, %29, %30, %31, %32, %33, %34, %35, %36, %37, %38, %39, %40, %41, %42, %43, %44, %45, %46, %47, %48, %49, %50, %51, %52, %53, %54, %55, %56, %57, %58, %59, %60, %61, %62, %63, %64, %65, %66, %67, %68, %69, %70, %71, %72, %73, %74, %75, %76, %77, %78, %79, %80, %81, %82, %83, %84, %85, %86, %87, %88, %89, %90, %91, %92, %93, %94, %95, %96, %97, %98, %99, %100, %101, %102, %103, %104, %105, %106, %107, %108, %109, %110, %111}, {%112, %113, %114, %115}, db, p, 1, 1, 1;\n}\n"
    : "+f"(d[0]), "+f"(d[1]), "+f"(d[2]), "+f"(d[3]), "+f"(d[4]), "+f"(d[5]), "+f"(d[6]), "+f"(d[7]), "+f"(d[8]), "+f"(d[9]), "+f"(d[10]), "+f"(d[11]), "+f"(d[12]), "+f"(d[13]), "+f"(d[14]), "+f"(d[15]), "+f"(d[16]), "+f"(d[17]), "+f"(d[18]), "+f"(d[19]), "+f"(d[20]), "+f"(d[21]), "+f"(d[22]), "+f"(d[23]), "+f"(d[24]), "+f"(d[25]), "+f"(d[26]), "+f"(d[27]), "+f"(d[28]), "+f"(d[29]), "+f"(d[30]), "+f"(d[31]), "+f"(d[32]), "+f"(d[33]), "+f"(d[34]), "+f"(d[35]), "+f"(d[36]), "+f"(d[37]), "+f"(d[38]), "+f"(d[39]), "+f"(d[40]), "+f"(d[41]), "+f"(d[42]), "+f"(d[43]), "+f"(d[44]), "+f"(d[45]), "+f"(d[46]), "+f"(d[47]), "+f"(d[48]), "+f"(d[49]), "+f"(d[50]), "+f"(d[51]), "+f"(d[52]), "+f"(d[53]), "+f"(d[54]), "+f"(d[55]), "+f"(d[56]), "+f"(d[57]), "+f"(d[58]), "+f"(d[59]), "+f"(d[60]), "+f"(d[61]), "+f"(d[62]), "+f"(d[63]), "+f"(d[64]), "+f"(d[65]), "+f"(d[66]), "+f"(d[67]), "+f"(d[68]), "+f"(d[69]), "+f"(d[70]), "+f"(d[71]), "+f"(d[72]), "+f"(d[73]), "+f"(d[74]), "+f"(d[75]), "+f"(d[76]), "+f"(d[77]), "+f"(d[78]), "+f"(d[79]), "+f"(d[80]), "+f"(d[81]), "+f"(d[82]), "+f"(d[83]), "+f"(d[84]), "+f"(d[85]), "+f"(d[86]), "+f"(d[87]), "+f"(d[88]), "+f"(d[89]), "+f"(d[90]), "+f"(d[91]), "+f"(d[92]), "+f"(d[93]), "+f"(d[94]), "+f"(d[95]), "+f"(d[96]), "+f"(d[97]), "+f"(d[98]), "+f"(d[99]), "+f"(d[100]), "+f"(d[101]), "+f"(d[102]), "+f"(d[103]), "+f"(d[104]), "+f"(d[105]), "+f"(d[106]), "+f"(d[107]), "+f"(d[108]), "+f"(d[109]), "+f"(d[110]), "+f"(d[111])
    : "r"(a0), "r"(a1), "r"(a2), "r"(a3), "r"(db));
}
__device__ __forceinline__ void wgmma_rs_acc(float (&d)[32], uint32_t a0, uint32_t a1, uint32_t a2, uint32_t a3, uint32_t db) {
  asm volatile("{\n.reg .pred p;\n.reg .b64 db;\nsetp.ne.b32 p, 1, 0;\nmov.b64 db, {%36, 1073741888};\n"
    "wgmma.mma_async.sync.aligned.m64n64k16.f32.bf16.bf16 {%0, %1, %2, %3, %4, %5, %6, %7, %8, %9, %10, %11, %12, %13, %14, %15, %16, %17, %18, %19, %20, %21, %22, %23, %24, %25, %26, %27, %28, %29, %30, %31}, {%32, %33, %34, %35}, db, p, 1, 1, 1;\n}\n"
    : "+f"(d[0]), "+f"(d[1]), "+f"(d[2]), "+f"(d[3]), "+f"(d[4]), "+f"(d[5]), "+f"(d[6]), "+f"(d[7]), "+f"(d[8]), "+f"(d[9]), "+f"(d[10]), "+f"(d[11]), "+f"(d[12]), "+f"(d[13]), "+f"(d[14]), "+f"(d[15]), "+f"(d[16]), "+f"(d[17]), "+f"(d[18]), "+f"(d[19]), "+f"(d[20]), "+f"(d[21]), "+f"(d[22]), "+f"(d[23]), "+f"(d[24]), "+f"(d[25]), "+f"(d[26]), "+f"(d[27]), "+f"(d[28]), "+f"(d[29]), "+f"(d[30]), "+f"(d[31])
    : "r"(a0), "r"(a1), "r"(a2), "r"(a3), "r"(db));
}
__device__ __forceinline__ void wgmma_rs_set(float (&d)[32], uint32_t a0, uint32_t a1, uint32_t a2, uint32_t a3, uint32_t db) {
  asm volatile("{\n.reg .pred p;\n.reg .b64 db;\nsetp.ne.b32 p, 0, 0;\nmov.b64 db, {%36, 1073741888};\n"
    "wgmma.mma_async.sync.aligned.m64n64k16.f32.bf16.bf16 {%0, %1, %2, %3, %4, %5, %6, %7, %8, %9, %10, %11, %12, %13, %14, %15, %16, %17, %18, %19, %20, %21, %22, %23, %24, %25, %26, %27, %28, %29, %30, %31}, {%32, %33, %34, %35}, db, p, 1, 1, 1;\n}\n"
    : "+f"(d[0]), "+f"(d[1]), "+f"(d[2]), "+f"(d[3]), "+f"(d[4]), "+f"(d[5]), "+f"(d[6]), "+f"(d[7]), "+f"(d[8]), "+f"(d[9]), "+f"(d[10]), "+f"(d[11]), "+f"(d[12]), "+f"(d[13]), "+f"(d[14]), "+f"(d[15]), "+f"(d[16]), "+f"(d[17]), "+f"(d[18]), "+f"(d[19]), "+f"(d[20]), "+f"(d[21]), "+f"(d[22]), "+f"(d[23]), "+f"(d[24]), "+f"(d[25]), "+f"(d[26]), "+f"(d[27]), "+f"(d[28]), "+f"(d[29]), "+f"(d[30]), "+f"(d[31])
    : "r"(a0), "r"(a1), "r"(a2), "r"(a3), "r"(db));
}
__device__ __forceinline__ void wgmma_ss_set(float (&d)[32], uint32_t da, uint32_t db) {
  asm volatile("{\n.reg .pred p;\n.reg .b64 da, db;\nsetp.ne.b32 p, 0, 0;\nmov.b64 da, {%32, 1073741888};\nmov.b64 db, {%33, 1073741888};\n"
    "wgmma.mma_async.sync.aligned.m64n64k16.f32.bf16.bf16 {%0, %1, %2, %3, %4, %5, %6, %7, %8, %9, %10, %11, %12, %13, %14, %15, %16, %17, %18, %19, %20, %21, %22, %23, %24, %25, %26, %27, %28, %29, %30, %31}, da, db, p, 1, 1, 1, 1;\n}\n"
    : "+f"(d[0]), "+f"(d[1]), "+f"(d[2]), "+f"(d[3]), "+f"(d[4]), "+f"(d[5]), "+f"(d[6]), "+f"(d[7]), "+f"(d[8]), "+f"(d[9]), "+f"(d[10]), "+f"(d[11]), "+f"(d[12]), "+f"(d[13]), "+f"(d[14]), "+f"(d[15]), "+f"(d[16]), "+f"(d[17]), "+f"(d[18]), "+f"(d[19]), "+f"(d[20]), "+f"(d[21]), "+f"(d[22]), "+f"(d[23]), "+f"(d[24]), "+f"(d[25]), "+f"(d[26]), "+f"(d[27]), "+f"(d[28]), "+f"(d[29]), "+f"(d[30]), "+f"(d[31])
    : "r"(da), "r"(db));
}
__device__ __forceinline__ void wgmma_ss_acc(float (&d)[32], uint32_t da, uint32_t db) {
  asm volatile("{\n.reg .pred p;\n.reg .b64 da, db;\nsetp.ne.b32 p, 1, 0;\nmov.b64 da, {%32, 1073741888};\nmov.b64 db, {%33, 1073741888};\n"
    "wgmma.mma_async.sync.aligned.m64n64k16.f32.bf16.bf16 {%0, %1, %2, %3, %4, %5, %6, %7, %8, %9, %10, %11, %12, %13, %14, %15, %16, %17, %18, %19, %20, %21, %22, %23, %24, %25, %26, %27, %28, %29, %30, %31}, da, db, p, 1, 1, 1, 1;\n}\n"
    : "+f"(d[0]), "+f"(d[1]), "+f"(d[2]), "+f"(d[3]), "+f"(d[4]), "+f"(d[5]), "+f"(d[6]), "+f"(d[7]), "+f"(d[8]), "+f"(d[9]), "+f"(d[10]), "+f"(d[11]), "+f"(d[12]), "+f"(d[13]), "+f"(d[14]), "+f"(d[15]), "+f"(d[16]), "+f"(d[17]), "+f"(d[18]), "+f"(d[19]), "+f"(d[20]), "+f"(d[21]), "+f"(d[22]), "+f"(d[23]), "+f"(d[24]), "+f"(d[25]), "+f"(d[26]), "+f"(d[27]), "+f"(d[28]), "+f"(d[29]), "+f"(d[30]), "+f"(d[31])
    : "r"(da), "r"(db));
}

__device__ __forceinline__ void delay(uint32_t n) {
  uint32_t t0, t1;
  asm volatile("mov.u32 %0, %%clock;" : "=r"(t0));
  do { asm volatile("mov.u32 %0, %%clock;" : "=r"(t1)); } while (t1 - t0 < n);
}

struct Params {
  const __nv_bfloat16* wqkv;
  const __nv_bfloat16* wo;
  const __nv_bfloat16* w1;
  const __nv_bfloat16* b1;
  const __nv_bfloat16* w2;
  const __nv_bfloat16* b2;
  uint32_t role[64];
};

__device__ __forceinline__ int fresh_lane() { int l; asm volatile("mov.u32 %0, %%laneid;" : "=r"(l)); return l; }
#define LANE_VARS const int lane = fresh_lane(), gq = lane >> 2, tq = lane & 3, tid = warp * 32 + lane; (void)gq; (void)tq; (void)tid;
#define LMX ((lane & 15) * 128 + (((lane >> 4) ^ (lane & 7)) << 4))

__device__ __forceinline__ int chunk_of(int j, int i) {
  return i == 0 ? j : i - (i <= j ? 1 : 0);
}

struct Ctx {
  uint32_t sb;
  uint32_t desc;
  uint32_t piece;
  uint32_t pl;
  uint32_t wbar;
  uint32_t n;
  uint32_t layer;
  uint32_t tm;
  uint32_t low;
  uint4* gp;
  uint32_t fo;
  uint32_t rel;
  int j;
};

__device__ __forceinline__ void wait_unit(Ctx& c, int u) {
  mbar_wait(c.sb + OFF_BAR + (BAR_BFULL + u % NS) * 8, ((u / NS) & 1) ^ (u % NS < 4 ? c.layer : 0u), c.n);
}
__device__ __forceinline__ void arrive1(uint32_t bar) { if ((threadIdx.x & 31) == 0) mbar_arrive(bar); }
__device__ __forceinline__ void release_unit(const Ctx& c, int u) {
  if ((threadIdx.x & 30) == 0) asm volatile("mbarrier.arrive.shared::cluster.b64 _, [%0];" ::"r"(c.rel + u % NS * 8) : "memory");
}
__device__ __forceinline__ uint32_t unit_desc(const Ctx& c, int u) { return c.desc + (u % NS) * (2 * CH >> 4); }

__device__ __forceinline__ uint32_t tagged(uint32_t w, uint32_t tm) { uint32_t d; asm("lop3.b32 %0, %1, %2, 1, 0xd8;" : "=r"(d) : "r"(w), "r"(tm)); return d; }
__device__ __forceinline__ void send_flag(const Ctx& c, uint4* dst) {
  asm volatile("{\n.reg .pred p;\n.reg .b64 a;\nsetp.eq.u32 p, %3, 0;\nadd.s64 a, %0, %1;\n@p st.relaxed.gpu.global.u32 [a], %2;\n}"
               ::"l"(dst), "l"((uint64_t)c.fo), "r"(c.tm), "r"(threadIdx.x & 31) : "memory");
}
__device__ __forceinline__ void send_frag(const Ctx& c, uint32_t (&r)[16], int row) {
  uint4* dst = c.gp + row * ROW;
#pragma unroll
  for (int q = 0; q < 4; q++) {
    r[4 * q] = tagged(r[4 * q], c.tm);
    st_b128(dst + q * 32, r[4 * q], r[4 * q + 1], r[4 * q + 2], r[4 * q + 3]);
  }
  send_flag(c, dst);
}
__device__ __forceinline__ void unpark(const Ctx& c, uint32_t (&r)[16], int row) {
  const uint4* src = c.gp + (row + c.j) * ROW;
#pragma unroll
  for (int q = 0; q < 4; q++) ld_b128(src + q * 32, r[4 * q], r[4 * q + 1], r[4 * q + 2], r[4 * q + 3]);
}
__device__ __forceinline__ void untag(const Ctx& c, uint32_t (&r)[16]) {
#pragma unroll
  for (int q = 0; q < 4; q++) asm volatile("lop3.b32 %0, %0, %1, 1, 0xd8;" : "+r"(r[4 * q]) : "r"(c.low >> q));
}
__device__ __forceinline__ void load_item(Ctx& c, int e, int i, uint32_t (&r)[16]) {
  const int s = (i - 1) & 3;
  uint32_t a = c.pl + s * CH;
  if (e == 1 && i > 4) {
    mbar_wait(c.wbar + (3 + i) * 8, c.layer, c.n);
    a = c.pl - OFF_W + (i == 7 ? 0 : (3 + i) * CH);
  } else if (s == 3) {
    mbar_wait(c.wbar + 24, (e + 1) & 1, c.n);
  } else {
    mbar_wait(c.wbar + s * 8, (((e >= 2) + (i > 4)) & 1) ^ c.layer, c.n);
  }
#pragma unroll
  for (int q = 0; q < 4; q++) lds_u4(a + q * 512, r[4 * q], r[4 * q + 1], r[4 * q + 2], r[4 * q + 3]);
}
__device__ __forceinline__ void free_item(const Ctx& c, int i) { arrive1(c.wbar + 32 + ((i - 1) & 3) * 8); }
__device__ __forceinline__ void check_item(Ctx& c, uint32_t (&r)[16], int row0, int col) {
  asm volatile("{\n.reg .pred p;\n.reg .b32 t, u;\n.reg .b64 a, lo, hi;\n.reg .b128 w;\n"
               "LAB_CHECK:\nlop3.b32 t, %0, %4, %17, 0x7e;\nlop3.b32 u, %8, %12, %17, 0x7e;\nlop3.b32 t, t, u, 1, 0xa8;\n"
               "setp.ne.u32 p, t, 0;\nvote.sync.any.pred p, p, 0xffffffff;\n@!p bra LAB_OK;\n"
               "and.b32 t, %20, 7;\nadd.u32 t, t, %19;\nmad.wide.u32 a, t, 16512, %18;\n"
               "ld.relaxed.gpu.global.b128 w, [a];\nmov.b128 {lo, hi}, w;\nmov.b64 {%0, %1}, lo;\nmov.b64 {%2, %3}, hi;\n"
               "ld.relaxed.gpu.global.b128 w, [a + 512];\nmov.b128 {lo, hi}, w;\nmov.b64 {%4, %5}, lo;\nmov.b64 {%6, %7}, hi;\n"
               "ld.relaxed.gpu.global.b128 w, [a + 1024];\nmov.b128 {lo, hi}, w;\nmov.b64 {%8, %9}, lo;\nmov.b64 {%10, %11}, hi;\n"
               "ld.relaxed.gpu.global.b128 w, [a + 1536];\nmov.b128 {lo, hi}, w;\nmov.b64 {%12, %13}, lo;\nmov.b64 {%14, %15}, hi;\n"
               "add.u32 %16, %16, 16;\nsetp.lt.u32 p, %16, " SPIN_LIMIT ";\n@p bra LAB_CHECK;\nLAB_OK:\n}"
               : "+r"(r[0]), "+r"(r[1]), "+r"(r[2]), "+r"(r[3]), "+r"(r[4]), "+r"(r[5]), "+r"(r[6]), "+r"(r[7]), "+r"(r[8]), "+r"(r[9]),
                 "+r"(r[10]), "+r"(r[11]), "+r"(r[12]), "+r"(r[13]), "+r"(r[14]), "+r"(r[15]), "+r"(c.n)
               : "r"(c.tm), "l"(c.gp), "r"(row0), "r"(col) : "memory");
}
struct Stats { uint32_t rs0, rs1, nm0, nm1; };
__device__ __forceinline__ void center(uint32_t (&r)[16], const Stats& st) {
#pragma unroll
  for (int i = 0; i < 16; i++) r[i] = fma_bf16x2(r[i], (i & 1) ? st.rs1 : st.rs0, (i & 1) ? st.nm1 : st.nm0);
}

template <class F>
__device__ __forceinline__ Stats publish_ln(Ctx& c, const float (&v)[32], uint32_t (&xr)[16], int row, uint4* stp, float scale, F&& idle) {
  PROBE_DECL;
  PROBE(0);
  float s[4] = {0.f, 0.f, 0.f, 0.f};
#pragma unroll
  for (int i = 0; i < 8; i++) {
    s[0] += v[4 * i] + v[4 * i + 1];
    s[2] += v[4 * i + 2] + v[4 * i + 3];
    s[1] = fmaf(v[4 * i], v[4 * i], fmaf(v[4 * i + 1], v[4 * i + 1], s[1]));
    s[3] = fmaf(v[4 * i + 2], v[4 * i + 2], fmaf(v[4 * i + 3], v[4 * i + 3], s[3]));
  }
#pragma unroll
  for (int d = 1; d < 4; d <<= 1) {
#pragma unroll
    for (int e = 0; e < 4; e++) s[e] += __shfl_xor_sync(0xffffffffu, s[e], d);
  }
#pragma unroll
  for (int i = 0; i < 16; i++) xr[i] = pack_bf16(v[2 * i], v[2 * i + 1]);
  c.low = (xr[0] & 1) | (xr[4] & 1) << 1 | (xr[8] & 1) << 2 | (xr[12] & 1) << 3;
  const int lane = fresh_lane();
  stp += lane >> 2;
  if ((lane & 3) == 0) st_b128(stp + c.j * 64, tagged(__float_as_uint(s[0]), c.tm), __float_as_uint(s[1]), __float_as_uint(s[2]), __float_as_uint(s[3]));
  PROBE(1);
  stp += (lane & 3) * 128;
  uint32_t a[4], b[4];
  uint4* dst = c.gp + (row + c.j) * ROW;
#pragma unroll
  for (int q = 0; q < 4; q++) {
    if (q == PQ) {
      ld_b128(stp, a[0], a[1], a[2], a[3]);
      ld_b128(stp + 64, b[0], b[1], b[2], b[3]);
    }
    xr[4 * q] = tagged(xr[4 * q], c.tm);
    st_b128(dst + q * 32, xr[4 * q], xr[4 * q + 1], xr[4 * q + 2], xr[4 * q + 3]);
  }
  send_flag(c, dst);
  PROBE(2);
  idle();
  PROBE(3);
#pragma unroll 1
  while (again(differ(a[0], b[0], c.tm), c.n)) {
    ld_b128(stp, a[0], a[1], a[2], a[3]);
    ld_b128(stp + 64, b[0], b[1], b[2], b[3]);
  }
  PROBE(4);
#pragma unroll
  for (int e = 0; e < 4; e++) s[e] = __uint_as_float(a[e]) + __uint_as_float(b[e]);
#pragma unroll
  for (int d = 1; d < 4; d <<= 1) {
#pragma unroll
    for (int e = 0; e < 4; e++) s[e] += __shfl_xor_sync(0xffffffffu, s[e], d);
  }
  const float m0 = s[0] * (-1.f / 512.f), m1 = s[2] * (-1.f / 512.f);
  Stats st;
  const float r0 = scale * rsqrtf(fmaxf(fmaf(s[1], 1.f / 512.f, -m0 * m0), 0.f) + 1e-5f);
  const float r1 = scale * rsqrtf(fmaxf(fmaf(s[3], 1.f / 512.f, -m1 * m1), 0.f) + 1e-5f);
  st.rs0 = pack_bf16(r0, r0); st.rs1 = pack_bf16(r1, r1);
  const float c0 = m0 * bf_lo(st.rs0), c1 = m1 * bf_lo(st.rs1);
  st.nm0 = pack_bf16(c0, c0); st.nm1 = pack_bf16(c1, c1);
  center(xr, st);
  PROBE(5);
  PROBE(6);
  if (row == PROW) PROBE_OUT(0, 7);
  return st;
}

template <int NR>
__device__ __forceinline__ void mma4(float (&acc)[NR], const uint32_t (&a)[16], uint32_t db) {
#pragma unroll
  for (int ks = 0; ks < 4; ks++) wgmma_rs_acc(acc, a[4 * ks], a[4 * ks + 1], a[4 * ks + 2], a[4 * ks + 3], db + ks * 128);
}
__device__ __forceinline__ void mma4_set(float (&acc)[32], const uint32_t (&a)[16], uint32_t db) {
  wgmma_rs_set(acc, a[0], a[1], a[2], a[3], db);
#pragma unroll
  for (int ks = 1; ks < 4; ks++) wgmma_rs_acc(acc, a[4 * ks], a[4 * ks + 1], a[4 * ks + 2], a[4 * ks + 3], db + ks * 128);
}
struct Acc2 { float k[32], v[32]; };
__device__ __forceinline__ void mma4(Acc2& acc, const uint32_t (&a)[16], uint32_t db) {
#pragma unroll
  for (int ks = 0; ks < 4; ks++) {
    wgmma_rs_acc(acc.k, a[4 * ks], a[4 * ks + 1], a[4 * ks + 2], a[4 * ks + 3], db + ks * 128);
    wgmma_rs_acc(acc.v, a[4 * ks], a[4 * ks + 1], a[4 * ks + 2], a[4 * ks + 3], db + 512 + ks * 128);
  }
}
template <int C0, int C1>
__device__ __forceinline__ void q_pass(Ctx& c, float (&acc)[32], const uint32_t (&own)[16], const uint32_t (&R)[7][16]) {
  if (C0 == 0) wait_unit(c, 4);
  if (C0 <= 4 && C1 > 4) wait_unit(c, 5);
  wg_fence();
#pragma unroll
  for (int i = C0; i < C1; i++) {
    const uint32_t db = unit_desc(c, 4 + i / 4) + (i & 3) * 512;
    if (i == 0) mma4_set(acc, own, db); else mma4(acc, R[i > 0 ? i - 1 : 0], db);
  }
  wg_commit();
}
__device__ __forceinline__ void add_part(Ctx& c, int t, uint32_t (&r)[16], float (&sum)[32]) {
  check_item(c, r, EX_P + c.j * 8, c.j - t);
  free_item(c, t);
#pragma unroll
  for (int i = 0; i < 16; i++) { sum[2 * i] += bf_lo(r[i]); sum[2 * i + 1] += bf_hi(r[i]); }
  fence_regs(sum);
}
__device__ __forceinline__ void send_part(const Ctx& c, const float (&p)[32], int t) {
  uint32_t pk[16];
#pragma unroll
  for (int i = 0; i < 16; i++) pk[i] = pack_bf16(p[2 * i], p[2 * i + 1]);
  send_frag(c, pk, EX_P + ((c.j + 1 + t) & 7) * 8 + c.j);
}
template <int K0, int K1, bool SET>
__device__ __forceinline__ void ffn2_steps(float (&p)[32], const uint32_t (&h)[56], uint32_t db) {
#pragma unroll
  for (int ks = K0; ks < K1; ks++) {
    if (SET && ks == 0) wgmma_rs_set(p, h[0], h[1], h[2], h[3], db);
    else wgmma_rs_acc(p, h[4 * ks], h[4 * ks + 1], h[4 * ks + 2], h[4 * ks + 3], db + ks * 128);
  }
}
template <int T>
__device__ __forceinline__ void ffn2_chunk(Ctx& c, float (&p)[32], float (&q)[32], const uint32_t (&h)[56], float (&sum)[32]) {
  uint32_t r[16];
  wait_unit(c, 16 + T);
  wg_fence();
  ffn2_steps<0, 8, true>(p, h, unit_desc(c, 16 + T));
  wg_commit();
  if (T > LAG) load_item(c, 3, T - LAG, r);
  wg_wait<1>();
  fence_regs(q);
  release_unit(c, 15 + T);
  send_part(c, q, T - 1);
  wg_fence();
  ffn2_steps<8, 14, false>(p, h, unit_desc(c, 16 + T));
  wg_commit();
  if (T > LAG) add_part(c, T - LAG, r, sum);
}

__global__ void __cluster_dims__(2, 1, 1) __launch_bounds__(384, 1)
fused_kernel(const __grid_constant__ CUtensorMap tm_x, const __grid_constant__ CUtensorMap tm_out,
             const __grid_constant__ CUtensorMap tm_wqkv, const __grid_constant__ CUtensorMap tm_wo,
             const __grid_constant__ CUtensorMap tm_w1, const __grid_constant__ CUtensorMap tm_w2, const Params prm) {
  extern __shared__ __align__(1024) uint8_t smem[];
  const uint32_t sb = smem_u32(smem);
  const int warp = __shfl_sync(0xffffffffu, (int)threadIdx.x >> 5, 0);
  const int cl = blockIdx.x >> 1, rank = blockIdx.x & 1;
  const int role = prm.role[cl];
  const int j = role & 7;
  const int g = (role >> 3) * 2 + rank;
  const uint32_t bars = sb + OFF_BAR;

  if (warp == 8) {
    if (elect_one()) {
#pragma unroll
      for (int b = 0; b < 2 * NS; b++) mbar_init(bars + b * 8, b < NS ? 1 : 16);
      fence_init();
    }
    __syncwarp();
  } else if (warp == 9 || warp == 10) {
    const uint32_t wb = bars + (BAR_WFULL + (warp - 9) * 11) * 8;
    if (elect_one()) {
#pragma unroll
      for (int i = 0; i < 11; i++) mbar_init(wb + i * 8, (i & 4) ? 4 : 1);
      fence_init();
      mbar_expect_tx(wb + 24, 8192);
      tma_load2d(sb + OFF_W + 3 * CH + (warp - 9) * 8192, &tm_x, j * 64, g * 128 + (warp - 9) * 64, wb + 24);
    }
    __syncwarp();
  } else if (warp == 11) {
    const int lane = threadIdx.x & 31;
#pragma unroll
    for (int i = 0; i < 2; i++) st_b128(&g_st[0][g][j][lane + 32 * i], 0, 0, 0, 0);
    if (lane < 8) st_b128(&g_ex[g][EX_X + j][1024 + lane], 0, 0, 0, 0);
    if (elect_one()) {
      bulk_prefetch_l2((const char*)prm.wqkv + blockIdx.x * 12288, 12288);
      mbar_init(bars + BAR_Z * 8, 1);
      mbar_init(bars + BAR_Z * 8 + 8, 1);
      fence_init();
    }
    __syncwarp();
  } else {
    TS(warp >> 2, 60);
  }
  asm volatile("barrier.cluster.arrive.relaxed.aligned;\nbarrier.cluster.wait.aligned;" ::: "memory");

  if (warp >= 8) {
    asm volatile("setmaxnreg.dec.sync.aligned.u32 " HREGS ";");
    const int lane = threadIdx.x & 31;
    uint32_t spent = 0;
    if (warp == 8) {
      uint32_t slot = 0, ph = 0x1f;
#pragma unroll 1
      for (int it = 0; it < 24 * NLAYER; it++) {
        const int u = it >= 24 ? it - 24 : it;
        const uint32_t fb = bars + (BAR_BFULL + slot) * 8;
        const uint32_t dst = sb + OFF_B + slot * 2 * CH;
        mbar_wait(fb + NS * 8, (ph >> slot) & 1, spent);
        ph ^= 1u << slot;
        if (elect_one()) {
          if (u >= 16) {
            mbar_expect_tx(fb, 28672);
            tma_load2d_both(dst + rank * 14336, &tm_w2, ((j + u + 1) & 7) * 64, 224 * j + rank * 112, fb);
          } else {
            const CUtensorMap* m = u < 6 ? &tm_wqkv : u < 8 ? &tm_wo : &tm_w1;
            mbar_expect_tx(fb, 32768);
#pragma unroll
            for (int h = 0; h < 2; h++) {
              const int b = 2 * rank + h;
              const int ck = u < 4 ? 2 * u + rank : u < 8 ? 4 * u + b : u;
              const int c0 = u < 4 ? 64 * j + 512 + h * 512 : u < 8 ? 64 * j : 224 * j + 64 * b;
              tma_load2d_both(dst + b * 8192, m, c0, chunk_of(j, ck & 7) * 64, fb);
            }
          }
        }
        __syncwarp();
        if (++slot == NS || u == 23) slot = 0;
      }
    } else if (warp < 11) {
      const int w = warp - 9;
      const uint32_t wb = bars + (BAR_WFULL + w * 11) * 8, win = sb + OFF_W + w * 8192;
      uint32_t ph = 7;
      mbar_wait(wb + 24, 0, spent);
#pragma unroll 1
      for (int ex = 0; ex < 4 * NLAYER; ex++) {
        const int e = ex & 3;
        const uint32_t tag = (ex >> 2) ^ 1u;
        const uint4* base = &g_ex[g][e == 3 ? EX_P + j * 8 : e == 0 ? EX_X : 8 * e - 8][w * 512];
        const int li = min(lane >> 2, 6) + 1;
        const uint32_t* scout = (const uint32_t*)(base + (e == 3 ? (j - li) & 7 : chunk_of(j, li)) * ROW + 1024 - w * 510) + (lane & 3);
        const uint32_t step = e == 3 ? 7 : 1;
        uint32_t ck = e == 3 ? (j + 7) & 7 : chunk_of(j, 1);
#pragma unroll
        for (int i = 0; i < 4; i++) mbar_wait(wb + 32 + i * 8, (ph >> i) & 1, spent);
        ph ^= 15;
        if (elect_one()) {
#pragma unroll
          for (int i = 0; i < 4; i++) mbar_expect_tx(wb + i * 8, 8192);
          if (e == 1) {
#pragma unroll
            for (int i = 8; i < 11; i++) mbar_expect_tx(wb + i * 8, 8192);
          }
        }
        __syncwarp();
        uint32_t stale = 0xffffffffu;
        if (((PRIO_MASK >> e) & 1) && w == 1) bar_sync(2, 64);
#pragma unroll 1
        for (int i = 0; i < 28; i += 4) {
          const uint4* src = base + ck * ROW;
          const uint32_t s = (i >> 2) & 3;
          uint32_t dst = win + s * CH, fb = wb + s * 8;
          if (i >= 16 && e == 1) {
            dst = win - OFF_W + (i == 24 ? 0 : (8 + s) * CH);
            fb += 64;
          } else if (i >= 16) {
            mbar_wait(fb + 32, (ph >> s) & 1, spent);
            ph ^= 1u << s;
            if (elect_one()) mbar_expect_tx(fb, 8192);
            __syncwarp();
          }
#pragma unroll 1
          while (((stale >> i) & 15u) && (spent += 16) < 262144u) stale = __ballot_sync(0xffffffffu, (ld_relaxed(scout) ^ tag) & 1u);
          if (elect_one()) bulk_load(dst, src, 8192, fb);
          __syncwarp();
          if (ex == 4 + GT / 7) TS(2, 8 * w + 9 + i / 4);
          if (((PRIO_MASK >> e) & 1) && w == 0 && i == 4 * PRIO_AT - 4) bar_arrive(2, 64);
          ck = (ck + step) & 7;
          if (ck == j) ck++;
        }
      }
    } else {
      fence_gpu();
      __syncwarp();
      if (lane == 0) mbar_arrive(bars + BAR_Z * 8);
#pragma unroll
      for (int i = 0; i < 4; i++) {
        const int idx = lane + 32 * i;
        if (idx < 112) {
          const uint32_t bb = __ldg((const uint32_t*)(prm.b1 + j * 224) + idx);
          const uint32_t b0 = __float_as_uint(0.5f * bf_lo(bb)), b1 = __float_as_uint(0.5f * bf_hi(bb));
          sts_u4(sb + OFF_B1 + idx * 16, b0, b1, b0, b1);
        }
      }
      mbar_wait(bars + BAR_BFULL * 8, 0, spent);
      if (elect_one()) {
        const int b = blockIdx.x;
        asm volatile("prefetch.tensormap [%0];" ::"l"(&tm_wo) : "memory");
        asm volatile("prefetch.tensormap [%0];" ::"l"(&tm_w1) : "memory");
        asm volatile("prefetch.tensormap [%0];" ::"l"(&tm_w2) : "memory");
        asm volatile("prefetch.tensormap [%0];" ::"l"(&tm_out) : "memory");
        bulk_prefetch_l2((const char*)prm.wo + b * 4096, 4096);
        bulk_prefetch_l2((const char*)prm.w1 + b * 14336, 14336);
        bulk_prefetch_l2((const char*)prm.w2 + b * 14336, 14336);
      }
      __syncwarp();
#pragma unroll
      for (int i = 0; i < 4; i++) st_b128(&g_kvp[j][g][lane + 32 * i], 0, 0, 0, 0);
      if (lane < 16) st_b128(&g_kvz[j][g][lane], 0, 0, 0, 0);
#pragma unroll
      for (int i = 0; i < 2; i++) st_b128(&g_st[1][g][j][lane + 32 * i], 0, 0, 0, 0);
#pragma unroll 1
      for (int i = lane >> 3; i < 10; i += 4) st_b128(&g_ex[g][i < 2 ? 8 * i + j : EX_P + (i - 2) * 8 + j][1024 + (lane & 7)], 0, 0, 0, 0);
      fence_gpu();
      __syncwarp();
      if (lane == 0) mbar_arrive(bars + (BAR_Z + 1) * 8);
      TS(2, 4);
    }
  } else {
    const int wg = warp >> 2, wi = warp & 3;
    asm volatile("setmaxnreg.inc.sync.aligned.u32 " CREGS ";");
    Ctx c;
    c.sb = sb; c.desc = mk_desc(sb + OFF_B); c.piece = sb + OFF_W + warp * 2048; c.wbar = bars + (BAR_WFULL + wg * 11) * 8;
    c.pl = c.piece + (threadIdx.x & 31) * 16; c.gp = &g_ex[g][0][warp * 128 + (threadIdx.x & 31)];
    c.fo = 16384 + wg * 32 + wi * 4 - warp * 2048;
    asm("mapa.shared::cluster.u32 %0, %1, %2;" : "=r"(c.rel) : "r"(bars + BAR_BEMPTY * 8), "r"(threadIdx.x & 1));
    asm volatile("" : "+r"(c.pl), "+l"(c.gp), "+r"(c.rel));
    c.n = 0; c.j = j;
    uint4* const stb = &g_st[0][g][0][warp * 8];
    float xv[32];
    TS(wg, 0);
    {
      mbar_wait(c.wbar + 24, 0, c.n);
      const int lane = fresh_lane();
      uint32_t t[16];
#pragma unroll
      for (int i = 0; i < 4; i++) ldsm4(c.piece + 3 * CH + (LMX ^ (i << 5)), t[4 * i], t[4 * i + 1], t[4 * i + 2], t[4 * i + 3]);
      TS(wg, 1);
#pragma unroll
      for (int i = 0; i < 16; i++) { xv[2 * i] = bf_lo(t[i]); xv[2 * i + 1] = bf_hi(t[i]); }
      mbar_wait(bars + BAR_Z * 8, 0, c.n);
      if (D_X && wg == 1) delay(D_X);
    }

#pragma unroll 1
    for (int layer = 0; layer < NLAYER; layer++) {
      c.layer = layer;
      c.tm = layer - 1;
      uint32_t o[16];
      Acc2 acc;
      {
        uint32_t xr[16], R[7][16];
        float (&aq)[32] = acc.v;
        Stats st;
        {
          st = publish_ln(c, xv, xr, EX_X, stb, 1.f, [&] {
            if (layer == 0) free_item(c, 4);
            zero_regs(acc.k); zero_regs(acc.v);
            wait_unit(c, 0);
          });
          TS(wg, 36 + layer);
          wg_fence();
          mma4(acc, xr, unit_desc(c, 0));
          wg_commit();
          load_item(c, 0, 1, R[0]);
#pragma unroll
          for (int i = 1; i < 8; i++) {
            if (i > 1 && i < 7) load_item(c, 0, i + 1, R[i < 7 ? i : 0]);
            check_item(c, R[i - 1], EX_X, chunk_of(j, i));
            if (i < 4) free_item(c, i);
            if (GT == 0) TS(0, 48 + i);
            center(R[i - 1], st);
            if ((i & 1) == 0) wait_unit(c, i / 2);
            wg_fence();
            mma4(acc, R[i - 1], unit_desc(c, i / 2) + (i & 1) * 1024);
            wg_commit();
            if (i == 1) load_item(c, 0, 2, R[1]);
            if (i == 3 || i == 5) { wg_wait<2>(); release_unit(c, i / 2 - 1); }
          }
          if (wg == 1) bar_arrive(3, 256);
          wg_wait<0>();
          fence_regs(acc.k); fence_regs(acc.v);
          release_unit(c, 2);
          release_unit(c, 3);
          TS(wg, 2 + layer * 16);
          LANE_VARS
          uint32_t t[16];
#pragma unroll
          for (int b = 0; b < 8; b++) {
            t[2 * b] = pack_bf16(acc.v[4 * b], acc.v[4 * b + 1]);
            t[2 * b + 1] = pack_bf16(acc.v[4 * b + 2], acc.v[4 * b + 3]);
          }
#pragma unroll
          for (int i = 0; i < 4; i++) stsm4(c.piece + CH + (LMX ^ (i << 5)), t[4 * i], t[4 * i + 1], t[4 * i + 2], t[4 * i + 3]);
          if (wg == 0) bar_sync(3, 256);
          q_pass<0, 2 * NQ>(c, aq, xr, R);
#pragma unroll
          for (int b = 0; b < 8; b++) {
            t[2 * b] = phi2(acc.k[4 * b], acc.k[4 * b + 1]);
            t[2 * b + 1] = phi2(acc.k[4 * b + 2], acc.k[4 * b + 3]);
          }
#pragma unroll
          for (int i = 0; i < 4; i++) stsm4(c.piece + (LMX ^ (i << 5)), t[4 * i], t[4 * i + 1], t[4 * i + 2], t[4 * i + 3]);
        }
        if (warp == 0) {
#pragma unroll
          for (int i = 0; i < 4; i++) sts_u4(c.pl + 2 * CH + i * 512, 0x3f803f80u, 0x3f803f80u, 0x3f803f80u, 0x3f803f80u);
        }
        fence_async_smem();
        {
          float (&akv)[32] = acc.k;
          bar_sync(1, 256);
          TS(wg, 3 + layer * 16);
          const uint32_t dk = c.desc + (OFF_KT >> 4), da = dk + ((wg + 1) * CH >> 4), ds = wg ? 0 : 128;
          wg_fence();
          wgmma_ss_set(akv, da, dk);
#pragma unroll
          for (int ks = 1; ks < 8; ks++) wgmma_ss_acc(akv, da + ks * ds, dk + ks * 128);
          wg_commit();
          q_pass<2 * NQ, 2 * NQ + 2>(c, aq, xr, R);
          if (layer == 0) mbar_wait(bars + (BAR_Z + 1) * 8, 0, c.n);
          wg_wait<1>();
          fence_regs(akv);
          LANE_VARS
          const int sel = wg ? gq : wi;
          float e[8];
#pragma unroll
          for (int i = 0; i < 8; i++) {
            const float lo = (sel & 1) ? akv[8 + i] : akv[i], hi = (sel & 1) ? akv[24 + i] : akv[16 + i];
            e[i] = (sel & 2) ? hi : lo;
          }
          if (wg == 0) st_b128(&g_kvp[j][g][tid], tagged(pack_bf16(e[0], e[1]), c.tm), pack_bf16(e[2], e[3]), pack_bf16(e[4], e[5]), pack_bf16(e[6], e[7]));
          else if (tid < 144) st_b128(&g_kvz[j][g][lane], tagged(__float_as_uint(e[0]), c.tm), __float_as_uint(e[1]), __float_as_uint(e[4]), __float_as_uint(e[5]));
        }
        TS(wg, 4 + layer * 16);
        q_pass<2 * NQ + 2, 8>(c, aq, xr, R);
        wg_wait<0>();
        fence_regs(aq);
        uint32_t pq[16];
        PROBE_DECL;
        LANE_VARS
        {
          uint32_t kv[9][4];
          const uint4* ksrc = &g_kvp[j][(lane >> 4) * 8][warp * 16 + (lane & 15)];
          const uint4* zsrc = &g_kvz[j][tid & 15][tid >> 4];
#pragma unroll
          for (int i = 0; i < 8; i++) ld_b128(ksrc + i * 128, kv[i][0], kv[i][1], kv[i][2], kv[i][3]);
          ld_b128(zsrc, kv[8][0], kv[8][1], kv[8][2], kv[8][3]);
#pragma unroll
          for (int b = 0; b < 8; b++) {
            pq[2 * b] = phi2(aq[4 * b], aq[4 * b + 1]);
            pq[2 * b + 1] = phi2(aq[4 * b + 2], aq[4 * b + 3]);
          }
#pragma unroll
          for (int i = 0; i < 16; i++) asm volatile("" : "+r"(pq[i]));
          TS(wg, 12 + layer * 16);
          PROBE(7);
#pragma unroll 1
          while (again((kv[8][0] ^ c.tm) | differ(kv[0][0], kv[1][0], c.tm) | differ(kv[2][0], kv[3][0], c.tm) |
                       differ(kv[4][0], kv[5][0], c.tm) | differ(kv[6][0], kv[7][0], c.tm), c.n)) {
#pragma unroll
            for (int i = 0; i < 8; i++) ld_b128(ksrc + i * 128, kv[i][0], kv[i][1], kv[i][2], kv[i][3]);
            ld_b128(zsrc, kv[8][0], kv[8][1], kv[8][2], kv[8][3]);
          }
          PROBE(8);
          uint32_t pk[4];
#pragma unroll
          for (int e = 0; e < 4; e++) {
            float lo = 0.f, hi = 0.f;
#pragma unroll
            for (int i = 0; i < 8; i++) { lo += bf_lo(kv[i][e]); hi += bf_hi(kv[i][e]); }
            lo += __shfl_xor_sync(0xffffffffu, lo, 16); hi += __shfl_xor_sync(0xffffffffu, hi, 16);
            pk[e] = pack_bf16(lo, hi);
          }
          sts_u4(sb + OFF_TB + (lane >> 4) * 8192 + (warp * 16 + (lane & 15)) * 16, pk[0], pk[1], pk[2], pk[3]);
          float zf[4];
#pragma unroll
          for (int e = 0; e < 4; e++) {
            zf[e] = __uint_as_float(kv[8][e]);
#pragma unroll
            for (int d = 1; d < 16; d <<= 1) zf[e] += __shfl_xor_sync(0xffffffffu, zf[e], d);
          }
          if ((lane & 14) == 0) sts_u2(sb + OFF_TB + (lane & 1) * 8192 + 2048 + (tid >> 4) * 8, pack_bf16(zf[0], zf[1]), pack_bf16(zf[2], zf[3]));
        }
        PROBE(9);
        bar_sync(1, 256);
        PROBE(10);
        TS(wg, 13 + layer * 16);
        free_item(c, 5); free_item(c, 6); free_item(c, 7);
#pragma unroll
        for (int h = 0; h < 4; h++) {
          const float4 kf = lds_f4(sb + OFF_TB + wg * 8192 + (h * 32 + lane) * 16);
          const float2 zf = lds_f2(sb + OFF_TB + wg * 8192 + 2048 + (h * 4 + tq) * 8);
          float n0[4] = {0.f, 0.f, 0.f, 0.f}, n1[4] = {0.f, 0.f, 0.f, 0.f}, dn[4] = {0.f, 0.f, 0.f, 0.f};
          mma16816(dn, pq[4 * h], pq[4 * h + 1], pq[4 * h + 2], pq[4 * h + 3], __float_as_uint(zf.x), __float_as_uint(zf.y));
          mma16816(n0, pq[4 * h], pq[4 * h + 1], pq[4 * h + 2], pq[4 * h + 3], __float_as_uint(kf.x), __float_as_uint(kf.z));
          mma16816(n1, pq[4 * h], pq[4 * h + 1], pq[4 * h + 2], pq[4 * h + 3], __float_as_uint(kf.y), __float_as_uint(kf.w));
          const float r0 = rcp_fast(dn[0] + 1e-6f), r1 = rcp_fast(dn[2] + 1e-6f);
          o[4 * h] = pack_bf16(n0[0] * r0, n0[1] * r0); o[4 * h + 1] = pack_bf16(n0[2] * r1, n0[3] * r1);
          o[4 * h + 2] = pack_bf16(n1[0] * r0, n1[1] * r0); o[4 * h + 3] = pack_bf16(n1[2] * r1, n1[3] * r1);
        }
        PROBE(11);
        if (D_O && wg == 1) delay(D_O);
        send_frag(c, o, EX_O + j);
        free_item(c, 4);
        PROBE(12);
        PROBE_OUT(7, 13);
        TS(wg, 5 + layer * 16);
      }

      {
        uint32_t R[7][16], xr[16];
        wait_unit(c, 6);
        wg_fence();
        mma4_set(acc.k, o, unit_desc(c, 6));
        wg_commit();
        unpark(c, xr, EX_X);
        wait_unit(c, 7);
        load_item(c, 1, 1, R[0]);
#pragma unroll
        for (int i = 1; i < 8; i++) {
          if (i < 7) load_item(c, 1, i + 1, R[i < 7 ? i : 0]);
          check_item(c, R[i - 1], EX_O, chunk_of(j, i));
          if (i < 5) free_item(c, i); else if (i > 5) release_unit(c, i - 2);
          if (GT == 7) TS(0, 48 + i);
          wg_fence();
          mma4(acc.k, R[i - 1], unit_desc(c, 6 + i / 4) + (i & 3) * 512);
          wg_commit();
          if (i == 5) { wg_wait<2>(); release_unit(c, 6); }
        }
        wg_wait<0>();
        fence_regs(acc.k);
        release_unit(c, 7);
        TS(wg, 6 + layer * 16);
        untag(c, xr);
#pragma unroll
        for (int i = 0; i < 16; i++) { xv[2 * i] = acc.k[2 * i] + bf_lo(xr[i]); xv[2 * i + 1] = acc.k[2 * i + 1] + bf_hi(xr[i]); }
      }

      {
        uint32_t h[56];
        float p0[32], p1[32];
        {
          float a[112];
          uint32_t R[2][16];
          const Stats st = publish_ln(c, xv, R[0], EX_X1, stb + NGRP * 512, 0.5f, [&] {
            const uint32_t tab = sb + OFF_B1 + (fresh_lane() & 3) * 16;
#pragma unroll
            for (int b = 0; b < 28; b++)
              asm volatile("ld.shared.v4.f32 {%0, %1, %2, %3}, [%4];" : "=f"(a[4 * b]), "=f"(a[4 * b + 1]), "=f"(a[4 * b + 2]), "=f"(a[4 * b + 3]) : "r"(tab + b * 64));
          });
          TS(wg, 38 + layer);
#pragma unroll
          for (int i = 0; i < 8; i++) {
            wait_unit(c, 8 + i);
            wg_fence();
            mma4(a, R[i & 1], unit_desc(c, 8 + i));
            wg_commit();
            if (i > 0) { wg_wait<1>(); release_unit(c, 7 + i); }
            if (i < 7) {
              load_item(c, 2, i + 1, R[~i & 1]);
              check_item(c, R[~i & 1], EX_X1, chunk_of(j, i + 1));
              free_item(c, i + 1);
              if (GT == 14) TS(0, 49 + i);
              center(R[~i & 1], st);
            }
          }
          wait_unit(c, 16);
          wait_unit(c, 17);
          zero_regs(p0); zero_regs(p1);
          LANE_VARS
          wg_wait<0>();
          fence_regs(a);
          release_unit(c, 15);
          TS(wg, 8 + layer * 16);
          uint32_t xr[16], bias2[8];
#pragma unroll
          for (int s = 0; s < 7; s++) {
#pragma unroll
            for (int i = 8 * s; i < 8 * s + 8; i++) h[i] = pack_bf16(gelu_half(a[2 * i]), gelu_half(a[2 * i + 1]));
            wg_fence();
#pragma unroll
            for (int ks = 2 * s; ks < 2 * s + 2; ks++) {
              wgmma_rs_acc(p0, h[4 * ks], h[4 * ks + 1], h[4 * ks + 2], h[4 * ks + 3], unit_desc(c, 16) + ks * 128);
              const int k1 = ks - LAGP;
              if (k1 >= 0) wgmma_rs_acc(p1, h[4 * (k1 > 0 ? k1 : 0)], h[4 * (k1 > 0 ? k1 : 0) + 1], h[4 * (k1 > 0 ? k1 : 0) + 2], h[4 * (k1 > 0 ? k1 : 0) + 3], unit_desc(c, 17) + k1 * 128);
            }
            wg_commit();
            if (s == 4) {
              unpark(c, xr, EX_X1);
#pragma unroll
              for (int i = 0; i < 8; i++) bias2[i] = __ldg((const uint32_t*)(prm.b2 + j * 64) + 4 * i + tq);
            }
          }
          wg_fence();
          ffn2_steps<14 - LAGP, 14, false>(p1, h, unit_desc(c, 17));
          wg_commit();
          TS(wg, 10 + layer * 16);
          untag(c, xr);
#pragma unroll
          for (int i = 0; i < 8; i++) {
            xv[4 * i] = bf_lo(bias2[i]) + bf_lo(xr[2 * i]); xv[4 * i + 1] = bf_hi(bias2[i]) + bf_hi(xr[2 * i]);
            xv[4 * i + 2] = bf_lo(bias2[i]) + bf_lo(xr[2 * i + 1]); xv[4 * i + 3] = bf_hi(bias2[i]) + bf_hi(xr[2 * i + 1]);
          }
        }
        wg_wait<1>();
        fence_regs(p0);
        release_unit(c, 16);
        send_part(c, p0, 0);
        ffn2_chunk<2>(c, p0, p1, h, xv);
        ffn2_chunk<3>(c, p1, p0, h, xv);
        TS(wg, 9 + layer * 16);
        ffn2_chunk<4>(c, p0, p1, h, xv);
        ffn2_chunk<5>(c, p1, p0, h, xv);
        ffn2_chunk<6>(c, p0, p1, h, xv);
        ffn2_chunk<7>(c, p1, p0, h, xv);
        TS(wg, 11 + layer * 16);
        {
          uint32_t r[2][16];
          load_item(c, 3, 8 - LAG, r[LAG & 1]);
#pragma unroll
          for (int u = 8 - LAG; u < 8; u++) {
            if (u < 6) load_item(c, 3, u + 1, r[~u & 1]);
            add_part(c, u, r[u & 1], xv);
            if (u == 6) load_item(c, 3, u + 1, r[~u & 1]);
          }
        }
        TS(wg, 32 + layer);
        wg_wait<0>();
        fence_regs(p1);
        release_unit(c, 23);
#pragma unroll
        for (int i = 0; i < 32; i++) xv[i] += p1[i];
        TS(wg, 34 + layer);
      }
    }
    asm volatile("barrier.cluster.arrive.relaxed.aligned;" ::: "memory");
    {
      const int lane = fresh_lane();
#pragma unroll
      for (int i = 0; i < 4; i++)
        stsm4(c.piece + (LMX ^ (i << 5)), pack_bf16(xv[8 * i], xv[8 * i + 1]), pack_bf16(xv[8 * i + 2], xv[8 * i + 3]),
              pack_bf16(xv[8 * i + 4], xv[8 * i + 5]), pack_bf16(xv[8 * i + 6], xv[8 * i + 7]));
    }
    fence_async_smem();
    __syncwarp();
    if (elect_one()) {
      tma_store2d(&tm_out, j * 64, g * 128 + warp * 16, c.piece);
      asm volatile("cp.async.bulk.commit_group;\ncp.async.bulk.wait_group.read 0;" ::: "memory");
    }
    __syncwarp();
    asm volatile("barrier.cluster.wait.aligned;" ::: "memory");
    TS(wg, 63);
  }
}

typedef CUresult (*EncodeFn)(CUtensorMap*, CUtensorMapDataType, cuuint32_t, void*, const cuuint64_t*, const cuuint64_t*,
                             const cuuint32_t*, const cuuint32_t*, CUtensorMapInterleave, CUtensorMapSwizzle,
                             CUtensorMapL2promotion, CUtensorMapFloatOOBfill);

void make_map(EncodeFn enc, CUtensorMap* m, const void* ptr, int cols, int rows, int box_rows) {
  cuuint64_t gd[2] = {(cuuint64_t)cols, (cuuint64_t)rows};
  cuuint64_t gs[1] = {(cuuint64_t)cols * 2};
  cuuint32_t bx[2] = {64, (cuuint32_t)box_rows};
  cuuint32_t es[2] = {1, 1};
  enc(m, CU_TENSOR_MAP_DATA_TYPE_BFLOAT16, 2, const_cast<void*>(ptr), gd, gs, bx, es, CU_TENSOR_MAP_INTERLEAVE_NONE,
      CU_TENSOR_MAP_SWIZZLE_128B, CU_TENSOR_MAP_L2_PROMOTION_L2_256B, CU_TENSOR_MAP_FLOAT_OOB_FILL_NONE);
}

}

extern "C" void kernel_launch(void* const* d_in, const int* in_sizes, int n_in, void* d_out, int out_size) {
  (void)in_sizes; (void)n_in; (void)out_size;
  static EncodeFn enc = nullptr;
  if (!enc) {
    void* fn = nullptr;
    cudaDriverEntryPointQueryResult qr;
    cudaGetDriverEntryPoint("cuTensorMapEncodeTiled", &fn, cudaEnableDefault, &qr);
    enc = (EncodeFn)fn;
    cudaFuncSetAttribute(fused_kernel, cudaFuncAttributeMaxDynamicSharedMemorySize, SMEM_BYTES);
  }
  CUtensorMap tx, tout, twqkv, two, tw1, tw2;
  make_map(enc, &tx, d_in[0], 512, 2048, 64);
  make_map(enc, &tout, d_out, 512, 2048, 16);
  make_map(enc, &twqkv, d_in[1], 1536, 512, 64);
  make_map(enc, &two, d_in[2], 512, 512, 64);
  make_map(enc, &tw1, d_in[4], 1792, 512, 64);
  make_map(enc, &tw2, d_in[6], 512, 1792, 112);
  Params prm;
  prm.wqkv = (const __nv_bfloat16*)d_in[1];
  prm.wo = (const __nv_bfloat16*)d_in[2];
  prm.w1 = (const __nv_bfloat16*)d_in[4];
  prm.b1 = (const __nv_bfloat16*)d_in[5];
  prm.w2 = (const __nv_bfloat16*)d_in[6];
  prm.b2 = (const __nv_bfloat16*)d_in[7];
  for (int cl = 0; cl < 64; cl++) {
    const int pos = cl < 4 ? cl + 4 : cl < 36 ? (cl - 4) >> 3 : 4 + (cl - 36) / 7;
    const int set = cl < 4 ? 0 : cl < 36 ? (cl - 4) & 7 : 1 + (cl - 36) % 7;
    prm.role[cl] = set * 8 + pos;
  }
  fused_kernel<<<128, 384, SMEM_BYTES, cudaStreamPerThread>>>(tx, tout, twqkv, two, tw1, tw2, prm);
}
```

```cpp
#include <cuda_runtime.h>
#include <cuda_bf16.h>
#include <cuda.h>
#include <stdint.h>

namespace {

constexpr int NLAYER = 2;
constexpr int NGRP = 16;
constexpr int D_O = 1000;
constexpr int SPLIT = 2;
constexpr int LAG = 5;
constexpr int GC = 8;
constexpr int NS = 5;
constexpr int CH = 16384;

constexpr int OFF_B = 0;
constexpr int OFF_W = NS * 2 * CH;
constexpr int OFF_KT = OFF_W;
constexpr int OFF_VT = OFF_W + CH;
constexpr int OFF_ONE = OFF_W + 2 * CH;
constexpr int OFF_TB = OFF_W + 3 * CH;
constexpr int OFF_B1 = OFF_W + 4 * CH;
constexpr int OFF_B2 = OFF_B1 + 1792;
constexpr int OFF_BAR = OFF_B2 + 512;
constexpr int BAR_BFULL = 0;
constexpr int BAR_BEMPTY = BAR_BFULL + NS;
constexpr int BAR_WFULL = BAR_BEMPTY + NS;
constexpr int BAR_Z = BAR_WFULL + 16;
constexpr int NBAR = BAR_Z + 1;
constexpr int SMEM_BYTES = OFF_BAR + NBAR * 8;
static_assert(SMEM_BYTES <= 232448, "smem");

constexpr int EX_O = 0, EX_X1 = 8, EX_X = 16;
constexpr int EX_P = 24;
constexpr int ROW = 1032;
__device__ __align__(1024) uint4 g_ex[NGRP][88][ROW];
__device__ __align__(1024) uint4 g_st[2][NGRP][8][64];
__device__ __align__(1024) uint4 g_kvp[8][NGRP][128];
__device__ __align__(1024) uint4 g_kvz[8][NGRP][16];

__device__ __forceinline__ uint32_t smem_u32(const void* p) { return (uint32_t)__cvta_generic_to_shared(p); }
__device__ __forceinline__ void mbar_init(uint32_t a, uint32_t c) { asm volatile("mbarrier.init.shared::cta.b64 [%0], %1;" ::"r"(a), "r"(c) : "memory"); }
__device__ __forceinline__ void mbar_expect_tx(uint32_t a, uint32_t b) { asm volatile("mbarrier.arrive.expect_tx.shared::cta.b64 _, [%0], %1;" ::"r"(a), "r"(b) : "memory"); }
__device__ __forceinline__ void mbar_arrive(uint32_t a) { asm volatile("mbarrier.arrive.shared::cta.b64 _, [%0];" ::"r"(a) : "memory"); }
#define SPIN_LIMIT "262144"
__device__ __forceinline__ void mbar_wait(uint32_t a, uint32_t p, uint32_t& n) {
  asm volatile("{\n.reg .pred p, q;\nLAB_WAIT:\nmbarrier.try_wait.parity.shared::cta.b64 p, [%1], %2;\n"
               "add.u32 %0, %0, 1;\nsetp.lt.and.u32 q, %0, " SPIN_LIMIT ", !p;\n@q bra LAB_WAIT;\n}"
               : "+r"(n) : "r"(a), "r"(p) : "memory");
}
__device__ __forceinline__ bool again(uint32_t t, uint32_t& n) {
  uint32_t r;
  asm volatile("{\n.reg .pred p;\n.reg .b32 t;\nand.b32 t, %2, 1;\nsetp.ne.u32 p, t, 0;\nvote.sync.any.pred p, p, 0xffffffff;\n"
               "add.u32 %1, %1, 16;\nsetp.lt.and.u32 p, %1, " SPIN_LIMIT ", p;\nselp.u32 %0, 1, 0, p;\n}"
               : "=r"(r), "+r"(n) : "r"(t) : "memory");
  return r;
}
__device__ __forceinline__ uint32_t differ(uint32_t a, uint32_t b, uint32_t m) { uint32_t d; asm("lop3.b32 %0, %1, %2, %3, 0x7e;" : "=r"(d) : "r"(a), "r"(b), "r"(m)); return d; }
__device__ __forceinline__ bool elect_one() {
  uint32_t p;
  asm volatile("{\n.reg .pred P;\nelect.sync _|P, 0xffffffff;\nselp.u32 %0, 1, 0, P;\n}" : "=r"(p));
  return p;
}
__device__ __forceinline__ void tma_load2d(uint32_t dst, const CUtensorMap* m, int c0, int c1, uint32_t bar) {
  asm volatile("cp.async.bulk.tensor.2d.shared::cluster.global.mbarrier::complete_tx::bytes [%0], [%1, {%3, %4}], [%2];"
               ::"r"(dst), "l"(m), "r"(bar), "r"(c0), "r"(c1) : "memory");
}
__device__ __forceinline__ void tma_load2d_both(uint32_t dst, const CUtensorMap* m, int c0, int c1, uint32_t bar) {
  asm volatile("cp.async.bulk.tensor.2d.shared::cluster.global.mbarrier::complete_tx::bytes.multicast::cluster [%0], [%1, {%3, %4}], [%2], %5;"
               ::"r"(dst), "l"(m), "r"(bar), "r"(c0), "r"(c1), "h"((uint16_t)3) : "memory");
}
__device__ __forceinline__ void tma_store2d(const CUtensorMap* m, int c0, int c1, uint32_t src) {
  asm volatile("cp.async.bulk.tensor.2d.global.shared::cta.bulk_group [%0, {%2, %3}], [%1];" ::"l"(m), "r"(src), "r"(c0), "r"(c1) : "memory");
}
__device__ __forceinline__ void bulk_load(uint32_t dst, const void* src, uint32_t bytes, uint32_t bar) {
  asm volatile("cp.async.bulk.shared::cluster.global.mbarrier::complete_tx::bytes [%0], [%1], %2, [%3];" ::"r"(dst), "l"(src), "r"(bytes), "r"(bar) : "memory");
}
__device__ __forceinline__ uint64_t policy() {
  uint64_t a;
  asm("createpolicy.fractional.L2::evict_first.b64 %0, 1.0;" : "=l"(a));
  return a;
}
__device__ __forceinline__ void bulk_load(uint32_t dst, const void* src, uint32_t bytes, uint32_t bar, uint64_t pol) {
  asm volatile("cp.async.bulk.shared::cluster.global.mbarrier::complete_tx::bytes.L2::cache_hint [%0], [%1], %2, [%3], %4;" ::"r"(dst), "l"(src), "r"(bytes), "r"(bar), "l"(pol) : "memory");
}
__device__ __forceinline__ void bulk_prefetch_l2(const void* src, uint32_t bytes) {
  asm volatile("cp.async.bulk.prefetch.L2.global [%0], %1;" ::"l"(src), "r"(bytes) : "memory");
}
__device__ __forceinline__ void fence_init() { asm volatile("fence.mbarrier_init.release.cluster;\nfence.proxy.async.shared::cta;" ::: "memory"); }
__device__ __forceinline__ void fence_async_smem() { asm volatile("fence.proxy.async.shared::cta;" ::: "memory"); }
__device__ __forceinline__ void bar_sync(int id, int n) { asm volatile("bar.sync %0, %1;" ::"r"(id), "r"(n) : "memory"); }
__device__ __forceinline__ uint32_t ld_relaxed(const uint32_t* p) { uint32_t v; asm volatile("ld.relaxed.gpu.global.u32 %0, [%1];" : "=r"(v) : "l"(p) : "memory"); return v; }
__device__ __forceinline__ void st_b128(void* p, uint32_t a, uint32_t b, uint32_t c, uint32_t d) {
  asm volatile("{\n.reg .b64 lo, hi;\n.reg .b128 t;\nmov.b64 lo, {%1, %2};\nmov.b64 hi, {%3, %4};\nmov.b128 t, {lo, hi};\nst.relaxed.gpu.global.b128 [%0], t;\n}"
               ::"l"(p), "r"(a), "r"(b), "r"(c), "r"(d) : "memory");
}
__device__ __forceinline__ void ld_b128(const void* p, uint32_t& a, uint32_t& b, uint32_t& c, uint32_t& d) {
  asm volatile("{\n.reg .b64 lo, hi;\n.reg .b128 t;\nld.relaxed.gpu.global.b128 t, [%4];\nmov.b128 {lo, hi}, t;\nmov.b64 {%0, %1}, lo;\nmov.b64 {%2, %3}, hi;\n}"
               : "=r"(a), "=r"(b), "=r"(c), "=r"(d) : "l"(p) : "memory");
}
__device__ __forceinline__ float4 lds_f4(uint32_t a) { float4 v; asm volatile("ld.shared.v4.f32 {%0, %1, %2, %3}, [%4];" : "=f"(v.x), "=f"(v.y), "=f"(v.z), "=f"(v.w) : "r"(a)); return v; }
__device__ __forceinline__ float2 lds_f2(uint32_t a) { float2 v; asm volatile("ld.shared.v2.f32 {%0, %1}, [%2];" : "=f"(v.x), "=f"(v.y) : "r"(a)); return v; }
__device__ __forceinline__ void stsm4(uint32_t a, uint32_t r0, uint32_t r1, uint32_t r2, uint32_t r3) {
  asm volatile("stmatrix.sync.aligned.m8n8.x4.shared.b16 [%0], {%1, %2, %3, %4};" ::"r"(a), "r"(r0), "r"(r1), "r"(r2), "r"(r3) : "memory");
}
__device__ __forceinline__ void ldsm4(uint32_t a, uint32_t& r0, uint32_t& r1, uint32_t& r2, uint32_t& r3) {
  asm volatile("ldmatrix.sync.aligned.m8n8.x4.shared.b16 {%0, %1, %2, %3}, [%4];" : "=r"(r0), "=r"(r1), "=r"(r2), "=r"(r3) : "r"(a) : "memory");
}
__device__ __forceinline__ uint32_t pack_bf16(float lo, float hi) { uint32_t d; asm("cvt.rn.bf16x2.f32 %0, %1, %2;" : "=r"(d) : "f"(hi), "f"(lo)); return d; }
__device__ __forceinline__ float bf_lo(uint32_t w) { return __uint_as_float(w << 16); }
__device__ __forceinline__ float bf_hi(uint32_t w) { return __uint_as_float(w & 0xffff0000u); }
__device__ __forceinline__ void mma16816(float (&c)[4], uint32_t a0, uint32_t a1, uint32_t a2, uint32_t a3, uint32_t b0, uint32_t b1) {
  asm volatile("mma.sync.aligned.m16n8k16.row.col.f32.bf16.bf16.f32 {%0, %1, %2, %3}, {%4, %5, %6, %7}, {%8, %9}, {%0, %1, %2, %3};"
               : "+f"(c[0]), "+f"(c[1]), "+f"(c[2]), "+f"(c[3]) : "r"(a0), "r"(a1), "r"(a2), "r"(a3), "r"(b0), "r"(b1));
}
__device__ __forceinline__ void mma16816_new(float (&d)[4], uint32_t a0, uint32_t a1, uint32_t a2, uint32_t a3, uint32_t b0, uint32_t b1, float c0) {
  asm volatile("mma.sync.aligned.m16n8k16.row.col.f32.bf16.bf16.f32 {%0, %1, %2, %3}, {%4, %5, %6, %7}, {%8, %9}, {%10, %10, %10, %10};"
               : "=f"(d[0]), "=f"(d[1]), "=f"(d[2]), "=f"(d[3]) : "r"(a0), "r"(a1), "r"(a2), "r"(a3), "r"(b0), "r"(b1), "f"(c0));
}
__device__ __forceinline__ float ex2(float x) { float y; asm("ex2.approx.ftz.f32 %0, %1;" : "=f"(y) : "f"(x)); return y; }
__device__ __forceinline__ float tanh_fast(float x) { float y; asm("tanh.approx.f32 %0, %1;" : "=f"(y) : "f"(x)); return y; }
__device__ __forceinline__ float rcp_fast(float x) { float y; asm("rcp.approx.ftz.f32 %0, %1;" : "=f"(y) : "f"(x)); return y; }
__device__ __forceinline__ uint32_t phi2(float t0, float t1) {
  const uint32_t tt = pack_bf16(t0, t1), ee = pack_bf16(ex2(t0 * 1.4426950408889634f), ex2(t1 * 1.4426950408889634f));
  uint32_t d;
  asm("{\n.reg .b32 x, y;\nmax.bf16x2 x, %1, %3;\nmin.bf16x2 y, %2, %4;\nadd.rn.bf16x2 %0, x, y;\n}"
      : "=r"(d) : "r"(tt), "r"(ee), "r"(0x35863586u), "r"(0x3f803f80u));
  return d;
}
__device__ __forceinline__ uint32_t fma_bf16x2(uint32_t a, uint32_t b, uint32_t c) { uint32_t d; asm("fma.rn.bf16x2 %0, %1, %2, %3;" : "=r"(d) : "r"(a), "r"(b), "r"(c)); return d; }
__device__ __forceinline__ void bar_arrive(int id, int n) { asm volatile("bar.arrive %0, %1;" ::"r"(id), "r"(n) : "memory"); }
__device__ __forceinline__ void sts_u2(uint32_t a, uint32_t x, uint32_t y) { asm volatile("st.shared.v2.b32 [%0], {%1, %2};" ::"r"(a), "r"(x), "r"(y) : "memory"); }
__device__ __forceinline__ void sts_u4(uint32_t a, uint32_t x, uint32_t y, uint32_t z, uint32_t w) { asm volatile("st.shared.v4.b32 [%0], {%1, %2, %3, %4};" ::"r"(a), "r"(x), "r"(y), "r"(z), "r"(w) : "memory"); }
__device__ __forceinline__ void lds_u4(uint32_t a, uint32_t& x, uint32_t& y, uint32_t& z, uint32_t& w) { asm volatile("ld.shared.v4.b32 {%0, %1, %2, %3}, [%4];" : "=r"(x), "=r"(y), "=r"(z), "=r"(w) : "r"(a) : "memory"); }
constexpr float G_ALPHA = 0.3292034911525734f, G_K = 2.423681954311584f, G_BETA = 1.5188174288475842f;
__device__ __forceinline__ void wg_fence() { asm volatile("wgmma.fence.sync.aligned;" ::: "memory"); }
__device__ __forceinline__ void wg_commit() { asm volatile("wgmma.commit_group.sync.aligned;" ::: "memory"); }
template <int N> __device__ __forceinline__ void wg_wait() { asm volatile("wgmma.wait_group.sync.aligned %0;" ::"n"(N) : "memory"); }
template <int N> __device__ __forceinline__ void fence_regs(float (&d)[N]) {
#pragma unroll
  for (int i = 0; i < N; i++) asm volatile("" : "+f"(d[i])::"memory");
}
__device__ __forceinline__ uint32_t mk_desc(uint32_t addr) { return ((addr & 0x3FFFF) >> 4) | ((8192 >> 4) << 16); }
__device__ __forceinline__ void fence_gpu() { asm volatile("fence.acq_rel.gpu;" ::: "memory"); }

__device__ __forceinline__ void wgmma_rs_acc(float (&d)[112], uint32_t a0, uint32_t a1, uint32_t a2, uint32_t a3, uint32_t db) {
  asm volatile("{\n.reg .pred p;\n.reg .b64 db;\nsetp.ne.b32 p, 1, 0;\nmov.b64 db, {%116, 1073741888};\n"
    "wgmma.mma_async.sync.aligned.m64n224k16.f32.bf16.bf16 {%0, %1, %2, %3, %4, %5, %6, %7, %8, %9, %10, %11, %12, %13, %14, %15, %16, %17, %18, %19, %20, %21, %22, %23, %24, %25, %26, %27, %28, %29, %30, %31, %32, %33, %34, %35, %36, %37, %38, %39, %40, %41, %42, %43, %44, %45, %46, %47, %48, %49, %50, %51, %52, %53, %54, %55, %56, %57, %58, %59, %60, %61, %62, %63, %64, %65, %66, %67, %68, %69, %70, %71, %72, %73, %74, %75, %76, %77, %78, %79, %80, %81, %82, %83, %84, %85, %86, %87, %88, %89, %90, %91, %92, %93, %94, %95, %96, %97, %98, %99, %100, %101, %102, %103, %104, %105, %106, %107, %108, %109, %110, %111}, {%112, %113, %114, %115}, db, p, 1, 1, 1;\n}\n"
    : "+f"(d[0]), "+f"(d[1]), "+f"(d[2]), "+f"(d[3]), "+f"(d[4]), "+f"(d[5]), "+f"(d[6]), "+f"(d[7]), "+f"(d[8]), "+f"(d[9]), "+f"(d[10]), "+f"(d[11]), "+f"(d[12]), "+f"(d[13]), "+f"(d[14]), "+f"(d[15]), "+f"(d[16]), "+f"(d[17]), "+f"(d[18]), "+f"(d[19]), "+f"(d[20]), "+f"(d[21]), "+f"(d[22]), "+f"(d[23]), "+f"(d[24]), "+f"(d[25]), "+f"(d[26]), "+f"(d[27]), "+f"(d[28]), "+f"(d[29]), "+f"(d[30]), "+f"(d[31]), "+f"(d[32]), "+f"(d[33]), "+f"(d[34]), "+f"(d[35]), "+f"(d[36]), "+f"(d[37]), "+f"(d[38]), "+f"(d[39]), "+f"(d[40]), "+f"(d[41]), "+f"(d[42]), "+f"(d[43]), "+f"(d[44]), "+f"(d[45]), "+f"(d[46]), "+f"(d[47]), "+f"(d[48]), "+f"(d[49]), "+f"(d[50]), "+f"(d[51]), "+f"(d[52]), "+f"(d[53]), "+f"(d[54]), "+f"(d[55]), "+f"(d[56]), "+f"(d[57]), "+f"(d[58]), "+f"(d[59]), "+f"(d[60]), "+f"(d[61]), "+f"(d[62]), "+f"(d[63]), "+f"(d[64]), "+f"(d[65]), "+f"(d[66]), "+f"(d[67]), "+f"(d[68]), "+f"(d[69]), "+f"(d[70]), "+f"(d[71]), "+f"(d[72]), "+f"(d[73]), "+f"(d[74]), "+f"(d[75]), "+f"(d[76]), "+f"(d[77]), "+f"(d[78]), "+f"(d[79]), "+f"(d[80]), "+f"(d[81]), "+f"(d[82]), "+f"(d[83]), "+f"(d[84]), "+f"(d[85]), "+f"(d[86]), "+f"(d[87]), "+f"(d[88]), "+f"(d[89]), "+f"(d[90]), "+f"(d[91]), "+f"(d[92]), "+f"(d[93]), "+f"(d[94]), "+f"(d[95]), "+f"(d[96]), "+f"(d[97]), "+f"(d[98]), "+f"(d[99]), "+f"(d[100]), "+f"(d[101]), "+f"(d[102]), "+f"(d[103]), "+f"(d[104]), "+f"(d[105]), "+f"(d[106]), "+f"(d[107]), "+f"(d[108]), "+f"(d[109]), "+f"(d[110]), "+f"(d[111])
    : "r"(a0), "r"(a1), "r"(a2), "r"(a3), "r"(db));
}
__device__ __forceinline__ void wgmma_rs_acc(float (&d)[32], uint32_t a0, uint32_t a1, uint32_t a2, uint32_t a3, uint32_t db) {
  asm volatile("{\n.reg .pred p;\n.reg .b64 db;\nsetp.ne.b32 p, 1, 0;\nmov.b64 db, {%36, 1073741888};\n"
    "wgmma.mma_async.sync.aligned.m64n64k16.f32.bf16.bf16 {%0, %1, %2, %3, %4, %5, %6, %7, %8, %9, %10, %11, %12, %13, %14, %15, %16, %17, %18, %19, %20, %21, %22, %23, %24, %25, %26, %27, %28, %29, %30, %31}, {%32, %33, %34, %35}, db, p, 1, 1, 1;\n}\n"
    : "+f"(d[0]), "+f"(d[1]), "+f"(d[2]), "+f"(d[3]), "+f"(d[4]), "+f"(d[5]), "+f"(d[6]), "+f"(d[7]), "+f"(d[8]), "+f"(d[9]), "+f"(d[10]), "+f"(d[11]), "+f"(d[12]), "+f"(d[13]), "+f"(d[14]), "+f"(d[15]), "+f"(d[16]), "+f"(d[17]), "+f"(d[18]), "+f"(d[19]), "+f"(d[20]), "+f"(d[21]), "+f"(d[22]), "+f"(d[23]), "+f"(d[24]), "+f"(d[25]), "+f"(d[26]), "+f"(d[27]), "+f"(d[28]), "+f"(d[29]), "+f"(d[30]), "+f"(d[31])
    : "r"(a0), "r"(a1), "r"(a2), "r"(a3), "r"(db));
}
__device__ __forceinline__ void wgmma_rs_set(float (&d)[32], uint32_t a0, uint32_t a1, uint32_t a2, uint32_t a3, uint32_t db) {
  asm volatile("{\n.reg .pred p;\n.reg .b64 db;\nsetp.ne.b32 p, 0, 0;\nmov.b64 db, {%36, 1073741888};\n"
    "wgmma.mma_async.sync.aligned.m64n64k16.f32.bf16.bf16 {%0, %1, %2, %3, %4, %5, %6, %7, %8, %9, %10, %11, %12, %13, %14, %15, %16, %17, %18, %19, %20, %21, %22, %23, %24, %25, %26, %27, %28, %29, %30, %31}, {%32, %33, %34, %35}, db, p, 1, 1, 1;\n}\n"
    : "+f"(d[0]), "+f"(d[1]), "+f"(d[2]), "+f"(d[3]), "+f"(d[4]), "+f"(d[5]), "+f"(d[6]), "+f"(d[7]), "+f"(d[8]), "+f"(d[9]), "+f"(d[10]), "+f"(d[11]), "+f"(d[12]), "+f"(d[13]), "+f"(d[14]), "+f"(d[15]), "+f"(d[16]), "+f"(d[17]), "+f"(d[18]), "+f"(d[19]), "+f"(d[20]), "+f"(d[21]), "+f"(d[22]), "+f"(d[23]), "+f"(d[24]), "+f"(d[25]), "+f"(d[26]), "+f"(d[27]), "+f"(d[28]), "+f"(d[29]), "+f"(d[30]), "+f"(d[31])
    : "r"(a0), "r"(a1), "r"(a2), "r"(a3), "r"(db));
}
__device__ __forceinline__ void wgmma_ss_set(float (&d)[32], uint32_t da, uint32_t db) {
  asm volatile("{\n.reg .pred p;\n.reg .b64 da, db;\nsetp.ne.b32 p, 0, 0;\nmov.b64 da, {%32, 1073741888};\nmov.b64 db, {%33, 1073741888};\n"
    "wgmma.mma_async.sync.aligned.m64n64k16.f32.bf16.bf16 {%0, %1, %2, %3, %4, %5, %6, %7, %8, %9, %10, %11, %12, %13, %14, %15, %16, %17, %18, %19, %20, %21, %22, %23, %24, %25, %26, %27, %28, %29, %30, %31}, da, db, p, 1, 1, 1, 1;\n}\n"
    : "+f"(d[0]), "+f"(d[1]), "+f"(d[2]), "+f"(d[3]), "+f"(d[4]), "+f"(d[5]), "+f"(d[6]), "+f"(d[7]), "+f"(d[8]), "+f"(d[9]), "+f"(d[10]), "+f"(d[11]), "+f"(d[12]), "+f"(d[13]), "+f"(d[14]), "+f"(d[15]), "+f"(d[16]), "+f"(d[17]), "+f"(d[18]), "+f"(d[19]), "+f"(d[20]), "+f"(d[21]), "+f"(d[22]), "+f"(d[23]), "+f"(d[24]), "+f"(d[25]), "+f"(d[26]), "+f"(d[27]), "+f"(d[28]), "+f"(d[29]), "+f"(d[30]), "+f"(d[31])
    : "r"(da), "r"(db));
}
__device__ __forceinline__ void wgmma_ss_acc(float (&d)[32], uint32_t da, uint32_t db) {
  asm volatile("{\n.reg .pred p;\n.reg .b64 da, db;\nsetp.ne.b32 p, 1, 0;\nmov.b64 da, {%32, 1073741888};\nmov.b64 db, {%33, 1073741888};\n"
    "wgmma.mma_async.sync.aligned.m64n64k16.f32.bf16.bf16 {%0, %1, %2, %3, %4, %5, %6, %7, %8, %9, %10, %11, %12, %13, %14, %15, %16, %17, %18, %19, %20, %21, %22, %23, %24, %25, %26, %27, %28, %29, %30, %31}, da, db, p, 1, 1, 1, 1;\n}\n"
    : "+f"(d[0]), "+f"(d[1]), "+f"(d[2]), "+f"(d[3]), "+f"(d[4]), "+f"(d[5]), "+f"(d[6]), "+f"(d[7]), "+f"(d[8]), "+f"(d[9]), "+f"(d[10]), "+f"(d[11]), "+f"(d[12]), "+f"(d[13]), "+f"(d[14]), "+f"(d[15]), "+f"(d[16]), "+f"(d[17]), "+f"(d[18]), "+f"(d[19]), "+f"(d[20]), "+f"(d[21]), "+f"(d[22]), "+f"(d[23]), "+f"(d[24]), "+f"(d[25]), "+f"(d[26]), "+f"(d[27]), "+f"(d[28]), "+f"(d[29]), "+f"(d[30]), "+f"(d[31])
    : "r"(da), "r"(db));
}
__device__ __forceinline__ void wgmma_rs_new(float (&d)[32], uint32_t a0, uint32_t a1, uint32_t a2, uint32_t a3, uint32_t db) {
  asm volatile("{\n.reg .pred p;\n.reg .b64 db;\nsetp.ne.b32 p, 0, 0;\nmov.b64 db, {%36, 1073741888};\n"
    "wgmma.mma_async.sync.aligned.m64n64k16.f32.bf16.bf16 {%0, %1, %2, %3, %4, %5, %6, %7, %8, %9, %10, %11, %12, %13, %14, %15, %16, %17, %18, %19, %20, %21, %22, %23, %24, %25, %26, %27, %28, %29, %30, %31}, {%32, %33, %34, %35}, db, p, 1, 1, 1;\n}\n"
    : "=f"(d[0]), "=f"(d[1]), "=f"(d[2]), "=f"(d[3]), "=f"(d[4]), "=f"(d[5]), "=f"(d[6]), "=f"(d[7]), "=f"(d[8]), "=f"(d[9]), "=f"(d[10]), "=f"(d[11]), "=f"(d[12]), "=f"(d[13]), "=f"(d[14]), "=f"(d[15]), "=f"(d[16]), "=f"(d[17]), "=f"(d[18]), "=f"(d[19]), "=f"(d[20]), "=f"(d[21]), "=f"(d[22]), "=f"(d[23]), "=f"(d[24]), "=f"(d[25]), "=f"(d[26]), "=f"(d[27]), "=f"(d[28]), "=f"(d[29]), "=f"(d[30]), "=f"(d[31])
    : "r"(a0), "r"(a1), "r"(a2), "r"(a3), "r"(db));
}


__device__ __forceinline__ void delay(uint32_t n) {
  uint32_t t0, t1;
  asm volatile("mov.u32 %0, %%clock;" : "=r"(t0));
  do { asm volatile("mov.u32 %0, %%clock;" : "=r"(t1)); } while (t1 - t0 < n);
}

struct Params {
  const __nv_bfloat16* x;
  const __nv_bfloat16* wqkv;
  const __nv_bfloat16* wo;
  const __nv_bfloat16* w1;
  const __nv_bfloat16* b1;
  const __nv_bfloat16* w2;
  const __nv_bfloat16* b2;
  uint32_t role[64];
};

__device__ __forceinline__ int fresh_lane() { int l; asm volatile("mov.u32 %0, %%laneid;" : "=r"(l)); return l; }
#define LANE_VARS const int lane = fresh_lane(), gq = lane >> 2, tq = lane & 3, tid = warp * 32 + lane; (void)gq; (void)tq; (void)tid;
#define LMX ((lane & 15) * 128 + (((lane >> 4) ^ (lane & 7)) << 4))

__device__ __forceinline__ int chunk_of(int j, int i) {
  return i == 0 ? j : i - (i <= j ? 1 : 0);
}

struct Ctx {
  uint32_t sb;
  uint32_t desc;
  uint32_t piece;
  uint32_t pl;
  uint32_t wbar;
  uint32_t n;
  uint32_t layer;
  uint32_t tm;
  uint32_t low;
  uint4* gp;
  uint32_t fo;
  uint32_t rel;
  int j;
  uint32_t eye;
};

__device__ __forceinline__ void wait_unit(Ctx& c, int u) {
  mbar_wait(c.sb + OFF_BAR + (BAR_BFULL + u % NS) * 8, ((u / NS) & 1) ^ (u % NS < 4 ? c.layer : 0u), c.n);
}
__device__ __forceinline__ void arrive1(uint32_t bar) { if ((threadIdx.x & 31) == 0) mbar_arrive(bar); }
__device__ __forceinline__ void release_unit(const Ctx& c, int u) {
  if ((threadIdx.x & 30) == 0) asm volatile("mbarrier.arrive.shared::cluster.b64 _, [%0];" ::"r"(c.rel + u % NS * 8) : "memory");
}
__device__ __forceinline__ uint32_t unit_desc(const Ctx& c, int u) {
  uint32_t d = c.desc + (u % NS) * (2 * CH >> 4);
  asm volatile("" : "+r"(d));
  return d;
}

__device__ __forceinline__ void cut(const Ctx& c, int k) {
  asm volatile("{\n.reg .pred p;\nsetp.eq.u32 p, %0, %1;\nLAB_CUT:\n@p st.shared.b32 [%0], %0;\n@p bra LAB_CUT;\n}" ::"r"(c.rel), "r"(4 * k + 4));
}
__device__ __forceinline__ uint32_t tagged(uint32_t w, uint32_t tm) { uint32_t d; asm("lop3.b32 %0, %1, %2, 1, 0xd8;" : "=r"(d) : "r"(w), "r"(tm)); return d; }
__device__ __forceinline__ void send_flag(const Ctx& c, uint4* dst) {
  asm volatile("{\n.reg .pred p;\n.reg .b64 a;\nsetp.eq.u32 p, %3, 0;\nadd.s64 a, %0, %1;\n@p st.relaxed.gpu.global.u32 [a], %2;\n}"
               ::"l"(dst), "l"((uint64_t)c.fo), "r"(c.tm), "r"(threadIdx.x & 31) : "memory");
}
__device__ __forceinline__ void send_frag(const Ctx& c, uint32_t (&r)[16], int row) {
  uint4* dst = c.gp + row * ROW;
#pragma unroll
  for (int q = 0; q < 4; q++) {
    r[4 * q] = tagged(r[4 * q], c.tm);
    st_b128(dst + q * 32, r[4 * q], r[4 * q + 1], r[4 * q + 2], r[4 * q + 3]);
  }
  send_flag(c, dst);
}
__device__ __forceinline__ void unpark(const Ctx& c, uint32_t (&r)[16], int row) {
  const uint4* src = c.gp + (row + c.j) * ROW;
#pragma unroll
  for (int q = 0; q < 4; q++) ld_b128(src + q * 32, r[4 * q], r[4 * q + 1], r[4 * q + 2], r[4 * q + 3]);
}
__device__ __forceinline__ void untag(const Ctx& c, uint32_t (&r)[16]) {
#pragma unroll
  for (int q = 0; q < 4; q++)
    asm volatile("{\n.reg .b32 d;\nprmt.b32 d, %1, 0, %2;\nadd.u32 %0, %0, d;\n}" : "+r"(r[4 * q]) : "r"(c.low), "r"(0x8880 + 0x1111 * q));
}
__device__ __forceinline__ uint32_t four_bytes(const uint32_t (&d)[4]) {
  return __byte_perm(__byte_perm(d[0], d[1], 0x40), __byte_perm(d[2], d[3], 0x40), 0x5410);
}
__device__ __forceinline__ void load_item(Ctx& c, int e, int i, uint32_t (&r)[16]) {
  const int s = (i - 1) & 3;
  const uint32_t a = c.pl + s * CH;
  mbar_wait(c.wbar + s * 8, s == 3 ? e & 1 : i < 4, c.n);
#pragma unroll
  for (int q = 0; q < 4; q++) lds_u4(a + q * 512, r[4 * q], r[4 * q + 1], r[4 * q + 2], r[4 * q + 3]);
}
__device__ __forceinline__ void free_item(const Ctx& c, int i) { arrive1(c.wbar + 32 + ((i - 1) & 3) * 8); }
__device__ __forceinline__ void check_item(Ctx& c, uint32_t (&r)[16], int row0, int col) {
  asm volatile("{\n.reg .pred p;\n.reg .b32 t, u;\n.reg .b64 a, lo, hi;\n.reg .b128 w;\n"
               "LAB_CHECK:\nlop3.b32 t, %0, %4, %17, 0x7e;\nlop3.b32 u, %8, %12, %17, 0x7e;\nlop3.b32 t, t, u, 1, 0xa8;\n"
               "setp.ne.u32 p, t, 0;\nvote.sync.any.pred p, p, 0xffffffff;\n@!p bra LAB_OK;\n"
               "and.b32 t, %20, 7;\nadd.u32 t, t, %19;\nmad.wide.u32 a, t, 16512, %18;\n"
               "ld.relaxed.gpu.global.b128 w, [a];\nmov.b128 {lo, hi}, w;\nmov.b64 {%0, %1}, lo;\nmov.b64 {%2, %3}, hi;\n"
               "ld.relaxed.gpu.global.b128 w, [a + 512];\nmov.b128 {lo, hi}, w;\nmov.b64 {%4, %5}, lo;\nmov.b64 {%6, %7}, hi;\n"
               "ld.relaxed.gpu.global.b128 w, [a + 1024];\nmov.b128 {lo, hi}, w;\nmov.b64 {%8, %9}, lo;\nmov.b64 {%10, %11}, hi;\n"
               "ld.relaxed.gpu.global.b128 w, [a + 1536];\nmov.b128 {lo, hi}, w;\nmov.b64 {%12, %13}, lo;\nmov.b64 {%14, %15}, hi;\n"
               "add.u32 %16, %16, 16;\nsetp.lt.u32 p, %16, " SPIN_LIMIT ";\n@p bra LAB_CHECK;\nLAB_OK:\n}"
               : "+r"(r[0]), "+r"(r[1]), "+r"(r[2]), "+r"(r[3]), "+r"(r[4]), "+r"(r[5]), "+r"(r[6]), "+r"(r[7]), "+r"(r[8]), "+r"(r[9]),
                 "+r"(r[10]), "+r"(r[11]), "+r"(r[12]), "+r"(r[13]), "+r"(r[14]), "+r"(r[15]), "+r"(c.n)
               : "r"(c.tm), "l"(c.gp), "r"(row0), "r"(col) : "memory");
}
__device__ __forceinline__ uint32_t eye_frag(int lane) { return (lane >> 3) == (lane & 3) ? ((lane & 4) ? 0x3f800000u : 0x3f80u) : 0u; }
__device__ __forceinline__ void add_word(float* d, uint32_t r0, uint32_t r1, uint32_t r2, uint32_t r3, uint32_t eye) {
  asm volatile("mma.sync.aligned.m16n8k8.row.col.f32.bf16.bf16.f32 {%0, %1, %2, %3}, {%4, %5}, {%6}, {%0, %1, %2, %3};"
               : "+f"(d[0]), "+f"(d[1]), "+f"(d[2]), "+f"(d[3]) : "r"(r0), "r"(r1), "r"(eye));
  asm volatile("mma.sync.aligned.m16n8k8.row.col.f32.bf16.bf16.f32 {%0, %1, %2, %3}, {%4, %5}, {%6}, {%0, %1, %2, %3};"
               : "+f"(d[4]), "+f"(d[5]), "+f"(d[6]), "+f"(d[7]) : "r"(r2), "r"(r3), "r"(eye));
}
__device__ __forceinline__ void add_tile(float (&d)[32], const uint32_t (&r)[16], uint32_t eye) {
#pragma unroll
  for (int q = 0; q < 4; q++) add_word(d + 8 * q, r[4 * q], r[4 * q + 1], r[4 * q + 2], r[4 * q + 3], eye);
}
struct Stats { uint32_t rs0, rs1, nm0, nm1; };
__device__ __forceinline__ void center(uint32_t (&r)[16], const Stats& st) {
#pragma unroll
  for (int i = 0; i < 16; i++) r[i] = fma_bf16x2(r[i], (i & 1) ? st.rs1 : st.rs0, (i & 1) ? st.nm1 : st.nm0);
}

__device__ __forceinline__ Stats make_stats(const float (&s)[4], float scale) {
  const float m0 = s[0] * (-1.f / 512.f), m1 = s[2] * (-1.f / 512.f);
  Stats st;
  const float r0 = scale * rsqrtf(fmaxf(fmaf(s[1], 1.f / 512.f, -m0 * m0), 0.f) + 1e-5f);
  const float r1 = scale * rsqrtf(fmaxf(fmaf(s[3], 1.f / 512.f, -m1 * m1), 0.f) + 1e-5f);
  st.rs0 = pack_bf16(r0, r0); st.rs1 = pack_bf16(r1, r1);
  const float c0 = m0 * bf_lo(st.rs0), c1 = m1 * bf_lo(st.rs1);
  st.nm0 = pack_bf16(c0, c0); st.nm1 = pack_bf16(c1, c1);
  return st;
}

__device__ __forceinline__ void load_x(Ctx& c, int i, uint32_t (&r)[16]) {
  const int lane = fresh_lane();
#pragma unroll
  for (int q = 0; q < 4; q++) ldsm4(c.piece - OFF_W + (6 + i) * CH + (LMX ^ (q << 5)), r[4 * q], r[4 * q + 1], r[4 * q + 2], r[4 * q + 3]);
}
__device__ __forceinline__ Stats first_ln(Ctx& c, uint32_t (&xr)[16], uint4* stp) {
  const int lane = fresh_lane();
  float s1[4] = {0.f, 0.f, 0.f, 0.f}, q0[4] = {0.f, 0.f, 0.f, 0.f}, q1[4] = {0.f, 0.f, 0.f, 0.f};
  const uint32_t other = ((lane & 7) + (lane >> 4) * 8) * 128 + ((((lane >> 3) & 1) ^ (lane & 7)) << 4);
  float sa[4][4] = {}, qa[4][4] = {}, qb[4][4] = {};
#pragma unroll 1
  for (int i = 0; i < 8; i += 2) {
    mbar_wait(c.wbar + (i >> 1) * 8, 0, c.n);
    uint32_t r[8][4], t[8][4];
#pragma unroll
    for (int q = 0; q < 8; q++) {
      const uint32_t a = c.piece - OFF_W + (6 + i + q / 4) * CH;
      ldsm4(a + (LMX ^ ((q & 3) << 5)), r[q][0], r[q][1], r[q][2], r[q][3]);
      ldsm4(a + (other ^ ((q & 3) << 5)), t[q][0], t[q][1], t[q][2], t[q][3]);
    }
#pragma unroll
    for (int q = 0; q < 8; q++) {
      mma16816(sa[q & 3], r[q][0], r[q][1], r[q][2], r[q][3], 0x3f803f80u, 0x3f803f80u);
      mma16816(qa[q & 3], r[q][0], r[q][1], r[q][2], r[q][3], t[q][0], t[q][1]);
      mma16816(qb[q & 3], r[q][0], r[q][1], r[q][2], r[q][3], t[q][2], t[q][3]);
    }
  }
#pragma unroll
  for (int n = 0; n < 4; n++) {
    s1[0] += sa[n][0]; s1[2] += sa[n][2]; q0[0] += qa[n][0]; q0[1] += qa[n][1]; q1[2] += qb[n][2]; q1[3] += qb[n][3];
  }
  load_x(c, 0, xr);
  const int src = (lane & 28) | (lane >> 3);
  const float s[4] = {s1[0], __shfl_sync(0xffffffffu, (lane & 4) ? q0[1] : q0[0], src), s1[2], __shfl_sync(0xffffffffu, (lane & 4) ? q1[3] : q1[2], src)};
  if ((lane & 3) == 0) st_b128(stp + (lane >> 2) + c.j * 64, c.tm, 0, 0, 0);
  uint4* dst = c.gp + (EX_X + c.j) * ROW;
  uint32_t d[4];
#pragma unroll
  for (int q = 0; q < 4; q++) {
    const uint32_t w = tagged(xr[4 * q], c.tm);
    d[q] = xr[4 * q] - w;
    st_b128(dst + q * 32, w, xr[4 * q + 1], xr[4 * q + 2], xr[4 * q + 3]);
  }
  send_flag(c, dst);
  c.low = four_bytes(d);
  const Stats st = make_stats(s, 1.f);
  center(xr, st);
  return st;
}

template <class F>
__device__ __forceinline__ Stats publish_ln(Ctx& c, const float (&v)[32], uint32_t (&xr)[16], int row, uint4* stp, float scale, F&& idle) {
  float s[4] = {0.f, 0.f, 0.f, 0.f};
#pragma unroll
  for (int i = 0; i < 8; i++) {
    s[0] += v[4 * i] + v[4 * i + 1];
    s[2] += v[4 * i + 2] + v[4 * i + 3];
    s[1] = fmaf(v[4 * i], v[4 * i], fmaf(v[4 * i + 1], v[4 * i + 1], s[1]));
    s[3] = fmaf(v[4 * i + 2], v[4 * i + 2], fmaf(v[4 * i + 3], v[4 * i + 3], s[3]));
  }
#pragma unroll
  for (int d = 1; d < 4; d <<= 1) {
#pragma unroll
    for (int e = 0; e < 4; e++) s[e] += __shfl_xor_sync(0xffffffffu, s[e], d);
  }
#pragma unroll
  for (int i = 0; i < 16; i++) xr[i] = pack_bf16(v[2 * i], v[2 * i + 1]);
  const int lane = fresh_lane();
  stp += lane >> 2;
  if ((lane & 3) == 0) st_b128(stp + c.j * 64, tagged(__float_as_uint(s[0]), c.tm), __float_as_uint(s[1]), __float_as_uint(s[2]), __float_as_uint(s[3]));
  stp += (lane & 3) * 128;
  uint32_t a[4], b[4], d[4];
  uint4* dst = c.gp + (row + c.j) * ROW;
#pragma unroll
  for (int q = 0; q < 4; q++) {
    const uint32_t w = tagged(__byte_perm(__float_as_uint(v[8 * q]) + (c.layer << 16), xr[4 * q], 0x7632), c.tm);
    d[q] = xr[4 * q] - w;
    st_b128(dst + q * 32, w, xr[4 * q + 1], xr[4 * q + 2], xr[4 * q + 3]);
  }
  send_flag(c, dst);
  c.low = four_bytes(d);
  cut(c, 42 + row);
  idle();
  ld_b128(stp, a[0], a[1], a[2], a[3]);
  ld_b128(stp + 64, b[0], b[1], b[2], b[3]);
  cut(c, 41 + row);
#pragma unroll 1
  while (again(differ(a[0], b[0], c.tm), c.n)) {
    ld_b128(stp, a[0], a[1], a[2], a[3]);
    ld_b128(stp + 64, b[0], b[1], b[2], b[3]);
  }
#pragma unroll
  for (int e = 0; e < 4; e++) s[e] = __uint_as_float(a[e]) + __uint_as_float(b[e]);
#pragma unroll
  for (int d = 1; d < 4; d <<= 1) {
#pragma unroll
    for (int e = 0; e < 4; e++) s[e] += __shfl_xor_sync(0xffffffffu, s[e], d);
  }
  const Stats st = make_stats(s, scale);
  center(xr, st);
  return st;
}

template <int NR>
__device__ __forceinline__ void mma4(float (&acc)[NR], const uint32_t (&a)[16], uint32_t db) {
#pragma unroll
  for (int ks = 0; ks < 4; ks++) wgmma_rs_acc(acc, a[4 * ks], a[4 * ks + 1], a[4 * ks + 2], a[4 * ks + 3], db + ks * 128);
}
__device__ __forceinline__ void mma4_set(float (&acc)[32], const uint32_t (&a)[16], uint32_t db) {
  wgmma_rs_set(acc, a[0], a[1], a[2], a[3], db);
#pragma unroll
  for (int ks = 1; ks < 4; ks++) wgmma_rs_acc(acc, a[4 * ks], a[4 * ks + 1], a[4 * ks + 2], a[4 * ks + 3], db + ks * 128);
}
struct Acc2 { float k[32], v[32]; };
__device__ __forceinline__ void mma4(Acc2& acc, const uint32_t (&a)[16], uint32_t db) {
#pragma unroll
  for (int ks = 0; ks < 4; ks++) {
    wgmma_rs_acc(acc.k, a[4 * ks], a[4 * ks + 1], a[4 * ks + 2], a[4 * ks + 3], db + ks * 128);
    wgmma_rs_acc(acc.v, a[4 * ks], a[4 * ks + 1], a[4 * ks + 2], a[4 * ks + 3], db + 512 + ks * 128);
  }
}
template <int C0, int C1>
__device__ __forceinline__ void q_pass(Ctx& c, float (&acc)[32], const uint32_t (&own)[16], const uint32_t (&R)[7][16]) {
  if (C0 == 0) wait_unit(c, 4);
  if (C0 <= 4 && C1 > 4) wait_unit(c, 5);
  wg_fence();
#pragma unroll
  for (int i = C0; i < C1; i++) {
    const uint32_t db = unit_desc(c, 4 + i / 4) + (i & 3) * 512;
    if (i == 0) mma4_set(acc, own, db); else mma4(acc, R[i > 0 ? i - 1 : 0], db);
  }
  wg_commit();
}
__device__ __forceinline__ void take_part(Ctx& c, int t, uint32_t (&r)[16]) {
  int j = c.j;
  asm volatile("" : "+r"(j));
  check_item(c, r, EX_P + j * 8, j - t);
  free_item(c, t);
}
template <bool TC>
__device__ __forceinline__ void add_part(Ctx& c, int t, uint32_t (&r)[16], float (&sum)[32]) {
  int j = c.j;
  asm volatile("" : "+r"(j));
  check_item(c, r, EX_P + j * 8, j - t);
  free_item(c, t);
  if (TC) {
    add_tile(sum, r, c.eye);
  } else {
#pragma unroll
    for (int i = 0; i < 16; i++) { sum[2 * i] = fmaf(bf_lo(r[i]), G_BETA, sum[2 * i]); sum[2 * i + 1] = fmaf(bf_hi(r[i]), G_BETA, sum[2 * i + 1]); }
    fence_regs(sum);
  }
}
__device__ __forceinline__ void send_part(const Ctx& c, float (&p)[32], int t) {
  uint32_t pk[16];
#pragma unroll
  for (int i = 0; i < 16; i++) pk[i] = pack_bf16(p[2 * i], p[2 * i + 1]);
  int j = c.j;
  asm volatile("" : "+r"(j));
  send_frag(c, pk, EX_P + ((j + 1 + t) & 7) * 8 + j);
}
template <int K0, int K1, int SET>
__device__ __forceinline__ void ffn2_steps(float (&p)[32], const uint32_t (&h)[56], uint32_t db) {
#pragma unroll
  for (int ks = K0; ks < K1; ks++) {
    if (SET == 2 && ks == 0) wgmma_rs_new(p, h[0], h[1], h[2], h[3], db);
    else if (SET && ks == 0) wgmma_rs_set(p, h[0], h[1], h[2], h[3], db);
    else wgmma_rs_acc(p, h[4 * ks], h[4 * ks + 1], h[4 * ks + 2], h[4 * ks + 3], db + ks * 128);
  }
}
__device__ __forceinline__ void load_b2(const Ctx& c, float (&v)[32]) {
  const uint32_t tab = c.sb + OFF_B2 + (fresh_lane() & 3) * 16;
#pragma unroll
  for (int b = 0; b < 8; b++)
    asm volatile("ld.shared.v4.f32 {%0, %1, %2, %3}, [%4];" : "=f"(v[4 * b]), "=f"(v[4 * b + 1]), "=f"(v[4 * b + 2]), "=f"(v[4 * b + 3]) : "r"(tab + b * 64));
}
template <int T>
__device__ __forceinline__ void ffn2_chunk(Ctx& c, float (&p)[32], float (&q)[32], const uint32_t (&h)[56], float (&sum)[32]) {
  uint32_t r[16];
  wait_unit(c, 16 + T);
  const uint32_t db = unit_desc(c, 16 + T);
  wg_fence();
  ffn2_steps<0, SPLIT, T == 1 ? 2 : 1>(p, h, db);
  wg_commit();
  if (T == LAG + 1) load_b2(c, sum);
  if (T > LAG) load_item(c, 3, T - LAG, r);
  wg_wait<1>();
  fence_regs(q);
  release_unit(c, 15 + T);
  send_part(c, q, T - 1);
  wg_fence();
  ffn2_steps<SPLIT, 14, 0>(p, h, db);
  wg_commit();
  if (T > LAG) add_part<false>(c, T - LAG, r, sum);
}

__global__ void __cluster_dims__(2, 1, 1) __launch_bounds__(384, 1)
fused_kernel(const __grid_constant__ CUtensorMap tm_x, const __grid_constant__ CUtensorMap tm_out,
             const __grid_constant__ CUtensorMap tm_wqkv, const __grid_constant__ CUtensorMap tm_wo,
             const __grid_constant__ CUtensorMap tm_w1, const __grid_constant__ CUtensorMap tm_w2, const Params prm) {
  extern __shared__ __align__(1024) uint8_t smem[];
  const uint32_t sb = smem_u32(smem);
  const int warp = __shfl_sync(0xffffffffu, (int)threadIdx.x >> 5, 0);
  const int cl = blockIdx.x >> 1, rank = blockIdx.x & 1;
  const int role = prm.role[cl];
  const int j = role & 7;
  const int g = (role >> 3) * 2 + rank;
  const uint32_t bars = sb + OFF_BAR;

  if (warp == 8) {
    if (elect_one()) {
#pragma unroll
      for (int b = 0; b < 2 * NS; b++) mbar_init(bars + b * 8, b < NS ? 1 : 16);
      fence_init();
    }
    __syncwarp();
  } else if (warp == 9 || warp == 10) {
    const uint32_t wb = bars + (BAR_WFULL + (warp - 9) * 8) * 8;
    if (elect_one()) {
#pragma unroll
      for (int i = 0; i < 8; i++) mbar_init(wb + i * 8, (i & 4) ? 4 : 1);
      fence_init();
#pragma unroll
      for (int i = 0; i < 4; i++) {
        mbar_expect_tx(wb + i * 8, 16384);
        tma_load2d(sb + (6 + i) * CH + (warp - 9) * 8192, &tm_x, chunk_of(j, i) * 64, g * 128 + (warp - 9) * 64, wb + (i >> 1) * 8);
      }
    }
    __syncwarp();
  } else if (warp == 11) {
    if (elect_one()) {
      bulk_prefetch_l2((const char*)prm.wqkv + blockIdx.x * 12288, 12288);
      mbar_init(bars + BAR_Z * 8, 1);
      fence_init();
    }
    __syncwarp();
  } else {
    if (warp == 0 && elect_one()) bulk_prefetch_l2((const char*)prm.x + blockIdx.x * 16384, 16384);
    if (warp == 1 && elect_one()) asm volatile("prefetch.tensormap [%0];" ::"l"(&tm_wqkv) : "memory");
  }
  asm volatile("barrier.cluster.arrive.relaxed.aligned;\nbarrier.cluster.wait.aligned;" ::: "memory");

  if (warp >= 8) {
    asm volatile("setmaxnreg.dec.sync.aligned.u32 24;");
    const int lane = threadIdx.x & 31;
    uint32_t spent = 0;
    if (warp == 8) {
      uint32_t slot = 0, ph = 7;
#pragma unroll 1
      for (int it = 0; it < 24 * NLAYER; it++) {
        const int u = it >= 24 ? it - 24 : it;
        const uint32_t fb = bars + (BAR_BFULL + slot) * 8;
        const uint32_t dst = sb + OFF_B + slot * 2 * CH;
        mbar_wait(fb + NS * 8, (ph >> slot) & 1, spent);
        ph ^= 1u << slot;
        if (u == 11) bar_sync(2, 64);
        if (it == 24 + 3 || it == 2) bar_sync(4, 96);
        if (elect_one()) {
          if (u >= 16) {
            mbar_expect_tx(fb, 28672);
            tma_load2d_both(dst + rank * 14336, &tm_w2, ((j + u + 1) & 7) * 64, 224 * j + rank * 112, fb);
          } else {
            const CUtensorMap* m = u < 6 ? &tm_wqkv : u < 8 ? &tm_wo : &tm_w1;
            mbar_expect_tx(fb, 32768);
#pragma unroll
            for (int h = 0; h < 2; h++) {
              const int b = 2 * rank + h;
              const int ck = u < 4 ? 2 * u + rank : u < 8 ? 4 * u + b : u;
              const int c0 = u < 4 ? 64 * j + 512 + h * 512 : u < 8 ? 64 * j : 224 * j + 64 * b;
              tma_load2d_both(dst + b * 8192, m, c0, chunk_of(j, ck & 7) * 64, fb);
            }
          }
        }
        __syncwarp();
        if (++slot == NS || u == 23) slot = 0;
      }
    } else if (warp < 11) {
      const int w = warp - 9;
      const uint32_t wb = bars + (BAR_WFULL + w * 8) * 8, win = sb + OFF_W + w * 8192;
      uint32_t ph = 0;
      if (elect_one()) {
#pragma unroll
        for (int i = 4; i < 8; i++) {
          tma_load2d(sb + (6 + i) * CH + w * 8192, &tm_x, chunk_of(j, i) * 64, g * 128 + w * 64, wb + (i >> 1) * 8);
        }
      }
      __syncwarp();
      bar_arrive(4, 96);
#pragma unroll 1
      for (int ex = 1; ex < 4 * NLAYER; ex++) {
        const int e = ex & 3;
        const uint32_t tag = (ex >> 2) ^ 1u;
        const uint4* base = &g_ex[g][e == 3 ? EX_P + j * 8 : e == 0 ? EX_X : 8 * e - 8][w * 512];
        const int li = min(lane >> 2, 6) + 1;
        const uint32_t* scout = (const uint32_t*)(base + (e == 3 ? (j - li) & 7 : chunk_of(j, li)) * ROW + 1024 - w * 510) + (lane & 3);
        const uint32_t step = e == 3 ? 7 : 1;
        uint32_t ck = e == 3 ? (j + 7) & 7 : chunk_of(j, 1);
#pragma unroll
        for (int i = 0; i < 4; i++) mbar_wait(wb + 32 + i * 8, (ph >> i) & 1, spent);
        ph ^= 15;
        if (elect_one()) {
#pragma unroll
          for (int i = 0; i < 4; i++) mbar_expect_tx(wb + i * 8, 8192);
        }
        __syncwarp();
        uint32_t stale = 0xffffffffu;
#pragma unroll
        for (int i = 0; i < 7; i++) {
          const uint4* src = base + ck * ROW;
          const uint32_t s = i & 3;
          const uint32_t dst = win + s * CH, fb = wb + s * 8;
          if (i >= 4) {
            mbar_wait(fb + 32, (ph >> s) & 1, spent);
            ph ^= 1u << s;
            if (elect_one()) mbar_expect_tx(fb, 8192);
            __syncwarp();
          }
          if ((stale >> 4 * i) & 15u) {
#pragma unroll 1
            do {
              stale = __ballot_sync(0xffffffffu, (ld_relaxed(scout) ^ tag) & 1u);
            } while (((stale >> 4 * i) & 15u) && (spent += 16) < 262144u);
          }
          if (elect_one()) {
            if (e == 3) bulk_load(dst, src, 8192, fb, policy());
            else bulk_load(dst, src, 8192, fb);
          }
          __syncwarp();
          if (i == 3 && e == 2 && w == 0) bar_arrive(2, 64);
          if (i == 3 && ex == 4) bar_arrive(4, 96);
          ck = (ck + step) & 7;
          if (ck == j) ck++;
        }
      }
    } else {
#pragma unroll
      for (int i = 0; i < 4; i++) {
        const int idx = lane + 32 * i;
        if (idx < 112) {
          const uint32_t bb = __ldg((const uint32_t*)(prm.b1 + j * 224) + idx);
          const uint32_t b0 = __float_as_uint(G_ALPHA * bf_lo(bb)), b1 = __float_as_uint(G_ALPHA * bf_hi(bb));
          sts_u4(sb + OFF_B1 + idx * 16, b0, b1, b0, b1);
        }
      }
      {
        const uint32_t bb = __ldg((const uint32_t*)(prm.b2 + j * 64) + lane);
        sts_u4(sb + OFF_B2 + lane * 16, bb << 16, bb & 0xffff0000u, bb << 16, bb & 0xffff0000u);
      }
      mbar_wait(bars + BAR_BFULL * 8, 0, spent);
      if (elect_one()) {
        const int b = blockIdx.x;
        asm volatile("prefetch.tensormap [%0];" ::"l"(&tm_wo) : "memory");
        asm volatile("prefetch.tensormap [%0];" ::"l"(&tm_w1) : "memory");
        asm volatile("prefetch.tensormap [%0];" ::"l"(&tm_w2) : "memory");
        asm volatile("prefetch.tensormap [%0];" ::"l"(&tm_out) : "memory");
        bulk_prefetch_l2((const char*)prm.wo + b * 4096, 4096);
        bulk_prefetch_l2((const char*)prm.w1 + b * 14336, 14336);
        bulk_prefetch_l2((const char*)prm.w2 + b * 14336, 14336);
      }
      __syncwarp();
#pragma unroll
      for (int i = 0; i < 4; i++) st_b128(&g_kvp[j][g][lane + 32 * i], 0, 0, 0, 0);
      if (lane < 16) st_b128(&g_kvz[j][g][lane], 0, 0, 0, 0);
#pragma unroll
      for (int i = 0; i < 2; i++) st_b128(&g_st[1][g][j][lane + 32 * i], 0, 0, 0, 0);
#pragma unroll 1
      for (int i = lane >> 3; i < 10; i += 4) st_b128(&g_ex[g][i < 2 ? 8 * i + j : EX_P + (i - 2) * 8 + j][1024 + (lane & 7)], 0, 0, 0, 0);
      fence_gpu();
      __syncwarp();
      if (lane == 0) mbar_arrive(bars + BAR_Z * 8);
    }
  } else {
    const int wg = warp >> 2, wi = warp & 3;
    asm volatile("setmaxnreg.inc.sync.aligned.u32 240;");
    Ctx c;
    c.sb = sb; c.desc = mk_desc(sb + OFF_B); c.piece = sb + OFF_W + warp * 2048; c.wbar = bars + (BAR_WFULL + wg * 8) * 8;
    c.pl = c.piece + (threadIdx.x & 31) * 16; c.gp = &g_ex[g][0][warp * 128 + (threadIdx.x & 31)];
    c.fo = 16384 + wg * 32 + wi * 4 - warp * 2048;
    asm("mapa.shared::cluster.u32 %0, %1, %2;" : "=r"(c.rel) : "r"(bars + BAR_BEMPTY * 8), "r"(threadIdx.x & 1));
    asm volatile("" : "+r"(c.pl), "+l"(c.gp), "+r"(c.rel));
    c.n = 0; c.j = j;
    uint4* const stb = &g_st[0][g][0][warp * 8];
    float xv[32];

#pragma unroll 1
    for (int layer = 0; layer < NLAYER; layer++) {
      c.layer = layer;
      c.tm = layer - 1;
      uint32_t o[16];
      Acc2 acc;
      {
        uint32_t xr[16], R[7][16];
        float (&aq)[32] = acc.v;
        Stats st;
        {
          if (layer == 0) {
            st = first_ln(c, xr, stb);
            wait_unit(c, 0);
          } else {
            st = publish_ln(c, xv, xr, EX_X, stb, 1.f, [&] { wait_unit(c, 0); });
          }
          {
            const uint32_t db = unit_desc(c, 0);
            wg_fence();
            wgmma_rs_new(acc.k, xr[0], xr[1], xr[2], xr[3], db);
            wgmma_rs_new(acc.v, xr[0], xr[1], xr[2], xr[3], db + 512);
#pragma unroll
            for (int ks = 1; ks < 4; ks++) {
              wgmma_rs_acc(acc.k, xr[4 * ks], xr[4 * ks + 1], xr[4 * ks + 2], xr[4 * ks + 3], db + ks * 128);
              wgmma_rs_acc(acc.v, xr[4 * ks], xr[4 * ks + 1], xr[4 * ks + 2], xr[4 * ks + 3], db + 512 + ks * 128);
            }
            wg_commit();
          }
          if (layer) load_item(c, 0, 1, R[0]); else load_x(c, 1, R[0]);
#pragma unroll
          for (int i = 1; i < 8; i++) {
            if (layer) {
              if (i > 1 && i < 7) load_item(c, 0, i + 1, R[i < 7 ? i : 0]);
              check_item(c, R[i - 1], EX_X, chunk_of(j, i));
              if (i < 4) free_item(c, i);
            } else if (i > 1 && i < 7) {
              load_x(c, i + 1, R[i < 7 ? i : 0]);
            }
            center(R[i - 1], st);
            if ((i & 1) == 0) wait_unit(c, i / 2);
            wg_fence();
            mma4(acc, R[i - 1], unit_desc(c, i / 2) + (i & 1) * 1024);
            wg_commit();
            if (i == 1) { if (layer) load_item(c, 0, 2, R[1]); else load_x(c, 2, R[1]); }
            if ((i == 1 || i == 3) && layer == 0) release_unit(c, 3 + i / 2);
            if (i == 3 || i == 5) { wg_wait<2>(); release_unit(c, i / 2 - 1); }
          }
          if (wg == 1) bar_arrive(3, 256);
          wg_wait<0>();
          fence_regs(acc.k); fence_regs(acc.v);
          release_unit(c, 2);
          release_unit(c, 3);
          LANE_VARS
          uint32_t t[16];
#pragma unroll
          for (int b = 0; b < 8; b++) {
            t[2 * b] = pack_bf16(acc.v[4 * b], acc.v[4 * b + 1]);
            t[2 * b + 1] = pack_bf16(acc.v[4 * b + 2], acc.v[4 * b + 3]);
          }
#pragma unroll
          for (int i = 0; i < 4; i++) stsm4(c.piece + CH + (LMX ^ (i << 5)), t[4 * i], t[4 * i + 1], t[4 * i + 2], t[4 * i + 3]);
          if (wg == 0) bar_sync(3, 256);
          q_pass<0, 1>(c, aq, xr, R);
#pragma unroll
          for (int b = 0; b < 8; b++) {
            t[2 * b] = phi2(acc.k[4 * b], acc.k[4 * b + 1]);
            t[2 * b + 1] = phi2(acc.k[4 * b + 2], acc.k[4 * b + 3]);
          }
#pragma unroll
          for (int i = 0; i < 4; i++) stsm4(c.piece + (LMX ^ (i << 5)), t[4 * i], t[4 * i + 1], t[4 * i + 2], t[4 * i + 3]);
        }
        if (warp == 0) {
#pragma unroll
          for (int i = 0; i < 4; i++) sts_u4(c.pl + 2 * CH + i * 512, 0x3f803f80u, 0x3f803f80u, 0x3f803f80u, 0x3f803f80u);
        }
        fence_async_smem();
        {
          float (&akv)[32] = acc.k;
          bar_sync(1, 256);
          const uint32_t dk = c.desc + (OFF_KT >> 4), da = dk + ((wg + 1) * CH >> 4), ds = wg ? 0 : 128;
          wg_fence();
          wgmma_ss_set(akv, da, dk);
#pragma unroll
          for (int ks = 1; ks < 8; ks++) wgmma_ss_acc(akv, da + ks * ds, dk + ks * 128);
          wg_commit();
          q_pass<1, 4>(c, aq, xr, R);
          if (layer == 0) mbar_wait(bars + BAR_Z * 8, 0, c.n);
          wg_wait<1>();
          fence_regs(akv);
          LANE_VARS
          const int sel = wg ? gq : wi;
          float e[8];
#pragma unroll
          for (int i = 0; i < 8; i++) {
            const float lo = (sel & 1) ? akv[8 + i] : akv[i], hi = (sel & 1) ? akv[24 + i] : akv[16 + i];
            e[i] = (sel & 2) ? hi : lo;
          }
          if (wg == 0) st_b128(&g_kvp[j][g][tid], tagged(pack_bf16(e[0], e[1]), c.tm), pack_bf16(e[2], e[3]), pack_bf16(e[4], e[5]), pack_bf16(e[6], e[7]));
          else if (tid < 144) st_b128(&g_kvz[j][g][lane], tagged(__float_as_uint(e[0]), c.tm), __float_as_uint(e[1]), __float_as_uint(e[4]), __float_as_uint(e[5]));
        }
        q_pass<4, 8>(c, aq, xr, R);
        wg_wait<1>();
        release_unit(c, 4);
        uint32_t pq[16];
        LANE_VARS
        {
          uint32_t kv[9][4];
          const uint4* ksrc = &g_kvp[j][(lane >> 4) * 8][warp * 16 + (lane & 15)];
          const uint4* zsrc = &g_kvz[j][tid & 15][tid >> 4];
          wg_wait<0>();
          fence_regs(aq);
#pragma unroll
          for (int i = 0; i < 8; i++) ld_b128(ksrc + i * 128, kv[i][0], kv[i][1], kv[i][2], kv[i][3]);
          ld_b128(zsrc, kv[8][0], kv[8][1], kv[8][2], kv[8][3]);
#pragma unroll
          for (int b = 0; b < 8; b++) {
            pq[2 * b] = phi2(aq[4 * b], aq[4 * b + 1]);
            pq[2 * b + 1] = phi2(aq[4 * b + 2], aq[4 * b + 3]);
          }
#pragma unroll
          for (int i = 0; i < 16; i++) asm volatile("" : "+r"(pq[i]));
          uint32_t dep = 0;
#pragma unroll
          for (int i = 0; i < 16; i++) dep |= pq[i];
          dep &= c.rel;
#pragma unroll 1
          while (again(dep | (kv[8][0] ^ c.tm) | differ(kv[0][0], kv[1][0], c.tm) | differ(kv[2][0], kv[3][0], c.tm) |
                       differ(kv[4][0], kv[5][0], c.tm) | differ(kv[6][0], kv[7][0], c.tm), c.n)) {
#pragma unroll
            for (int i = 0; i < 8; i++) ld_b128(ksrc + i * 128, kv[i][0], kv[i][1], kv[i][2], kv[i][3]);
            ld_b128(zsrc, kv[8][0], kv[8][1], kv[8][2], kv[8][3]);
          }
          uint32_t pk[4];
          {
            float t0[8] = {0.f, 0.f, 0.f, 0.f, 0.f, 0.f, 0.f, 0.f}, t1[8] = {0.f, 0.f, 0.f, 0.f, 0.f, 0.f, 0.f, 0.f};
            const uint32_t eye = eye_frag(lane);
#pragma unroll
            for (int i = 0; i < 8; i += 2) {
              add_word(t0, kv[i][0], kv[i][1], kv[i][2], kv[i][3], eye);
              add_word(t1, kv[i + 1][0], kv[i + 1][1], kv[i + 1][2], kv[i + 1][3], eye);
            }
#pragma unroll
            for (int e = 0; e < 8; e++) {
              t0[e] += t1[e];
              t0[e] += __shfl_xor_sync(0xffffffffu, t0[e], 16);
            }
#pragma unroll
            for (int e = 0; e < 4; e++) pk[e] = pack_bf16(t0[2 * e], t0[2 * e + 1]);
          }
          sts_u4(sb + OFF_TB + (lane >> 4) * 8192 + (warp * 16 + (lane & 15)) * 16, pk[0], pk[2], pk[1], pk[3]);
          float zf[4];
#pragma unroll
          for (int e = 0; e < 4; e++) {
            zf[e] = __uint_as_float(kv[8][e]);
#pragma unroll
            for (int d = 1; d < 16; d <<= 1) zf[e] += __shfl_xor_sync(0xffffffffu, zf[e], d);
          }
          if ((lane & 14) == 0) sts_u2(sb + OFF_TB + (lane & 1) * 8192 + 2048 + (tid >> 4) * 8, pack_bf16(zf[0], zf[1]), pack_bf16(zf[2], zf[3]));
        }
        bar_sync(1, 256);
        free_item(c, 5); free_item(c, 6); free_item(c, 7);
        release_unit(c, 5);
#pragma unroll
        for (int h = 0; h < 4; h++) {
          const float4 kf = lds_f4(sb + OFF_TB + wg * 8192 + (h * 32 + lane) * 16);
          const float2 zf = lds_f2(sb + OFF_TB + wg * 8192 + 2048 + (h * 4 + tq) * 8);
          float n0[4], n1[4], dn[4];
          mma16816_new(dn, pq[4 * h], pq[4 * h + 1], pq[4 * h + 2], pq[4 * h + 3], __float_as_uint(zf.x), __float_as_uint(zf.y), 1e-6f);
          mma16816_new(n0, pq[4 * h], pq[4 * h + 1], pq[4 * h + 2], pq[4 * h + 3], __float_as_uint(kf.x), __float_as_uint(kf.y), 0.f);
          mma16816_new(n1, pq[4 * h], pq[4 * h + 1], pq[4 * h + 2], pq[4 * h + 3], __float_as_uint(kf.z), __float_as_uint(kf.w), 0.f);
          const float r0 = rcp_fast(dn[0]), r1 = rcp_fast(dn[2]);
          o[4 * h] = pack_bf16(n0[0] * r0, n0[1] * r0); o[4 * h + 1] = pack_bf16(n0[2] * r1, n0[3] * r1);
          o[4 * h + 2] = pack_bf16(n1[0] * r0, n1[1] * r0); o[4 * h + 3] = pack_bf16(n1[2] * r1, n1[3] * r1);
        }
        if (wg == 1) delay(D_O);
        send_frag(c, o, EX_O + j);
        free_item(c, 4);
      }

      {
        uint32_t R[7][16], xr[16];
        wait_unit(c, 6);
        wg_fence();
        mma4_set(acc.k, o, unit_desc(c, 6));
        wg_commit();
        unpark(c, xr, EX_X);
        wait_unit(c, 7);
        wg_wait<0>();
        fence_regs(acc.k);
        untag(c, xr);
        add_tile(acc.k, xr, eye_frag(fresh_lane()));
#pragma unroll
        for (int i = 1; i < 4; i++) load_item(c, 1, i, R[i - 1]);
#pragma unroll
        for (int i = 1; i < 4; i++) {
          check_item(c, R[i - 1], EX_O, chunk_of(j, i));
          free_item(c, i);
        }
        load_item(c, 1, 4, R[3]);
        wg_fence();
#pragma unroll
        for (int i = 1; i < 4; i++) mma4(acc.k, R[i - 1], unit_desc(c, 6) + i * 512);
        wg_commit();
#pragma unroll
        for (int i = 4; i < 8; i++) {
          if (i < 7) load_item(c, 1, i + 1, R[i < 7 ? i : 0]);
          check_item(c, R[i - 1], EX_O, chunk_of(j, i));
          free_item(c, i);
          wg_fence();
          mma4(acc.k, R[i - 1], unit_desc(c, 7) + (i & 3) * 512);
          wg_commit();
          if (i == 4) { wg_wait<1>(); release_unit(c, 6); }
        }
        wg_wait<0>();
        fence_regs(acc.k);
        release_unit(c, 7);
#pragma unroll
        for (int i = 0; i < 32; i++) xv[i] = acc.k[i];
      }

      {
        uint32_t h[56], xr[16];
        float p0[32], p1[32];
        {
          float a[112];
          uint32_t R[2][16];
          const Stats st = publish_ln(c, xv, R[0], EX_X1, stb + NGRP * 512, G_ALPHA, [&] {
            const uint32_t tab = sb + OFF_B1 + (fresh_lane() & 3) * 16;
#pragma unroll
            for (int b = 0; b < 28; b++)
              asm volatile("ld.volatile.shared.v4.f32 {%0, %1, %2, %3}, [%4];" : "=f"(a[4 * b]), "=f"(a[4 * b + 1]), "=f"(a[4 * b + 2]), "=f"(a[4 * b + 3]) : "r"(tab + b * 64));
          });
#pragma unroll
          for (int i = 0; i < 8; i++) {
            wait_unit(c, 8 + i);
            if (i == 4 && wg == 1) bar_sync(6, 256);
            wg_fence();
            mma4(a, R[i & 1], unit_desc(c, 8 + i));
            wg_commit();
            if (i == 7 && wg == 0) bar_arrive(6, 256);
            if (i > 0) { wg_wait<1>(); release_unit(c, 7 + i); }
            if (i < 7) {
              load_item(c, 2, i + 1, R[~i & 1]);
              check_item(c, R[~i & 1], EX_X1, chunk_of(j, i + 1));
              free_item(c, i + 1);
              center(R[~i & 1], st);
            }
          }
          wg_wait<0>();
          fence_regs(a);
          release_unit(c, 15);
          {
            float t[GC];
#pragma unroll
            for (int i = 0; i < 112; i++) {
              float& v = t[i % GC];
              if (i < GC) v = fmaf(a[i], a[i], G_K);
              else asm("{\n.reg .pred p;\nsetp.ne.u32 p, %2, 0;\n@p fma.rn.f32 %0, %1, %1, %3;\n}" : "+f"(v) : "f"(a[i]), "r"(c.rel), "f"(G_K));
              v = fmaf(a[i], tanh_fast(v * a[i]), a[i]);
              if (i & 1) h[i / 2] = pack_bf16(t[(i - 1) % GC], v);
              if (i == 56) unpark(c, xr, EX_X1);
            }
          }
#pragma unroll
          for (int i = 0; i < 56; i++) asm volatile("" : "+r"(h[i]));
          wait_unit(c, 16);
          const uint32_t db = unit_desc(c, 16);
          wg_fence();
          ffn2_steps<0, 14, 2>(p0, h, db);
          wg_commit();
        }
        ffn2_chunk<1>(c, p1, p0, h, xv);
        ffn2_chunk<2>(c, p0, p1, h, xv);
        ffn2_chunk<3>(c, p1, p0, h, xv);
        ffn2_chunk<4>(c, p0, p1, h, xv);
        ffn2_chunk<5>(c, p1, p0, h, xv);
        ffn2_chunk<6>(c, p0, p1, h, xv);
        ffn2_chunk<7>(c, p1, p0, h, xv);
        {
          uint32_t r[2][16];
          load_item(c, 3, 8 - LAG, r[LAG & 1]);
          take_part(c, 8 - LAG, r[LAG & 1]);
          load_item(c, 3, 9 - LAG, r[~LAG & 1]);
          untag(c, xr);
          c.eye = eye_frag(fresh_lane());
          take_part(c, 9 - LAG, r[~LAG & 1]);
          add_tile(xv, xr, c.eye);
          wg_wait<0>();
          fence_regs(p1);
          release_unit(c, 23);
#pragma unroll
          for (int u = 8 - LAG; u < 8; u++) {
            if (u < 6 && u > 8 - LAG) load_item(c, 3, u + 1, r[~u & 1]);
            if (u <= 9 - LAG) add_tile(p1, r[u & 1], c.eye);
            else add_part<true>(c, u, r[u & 1], p1);
            if (u == 6) load_item(c, 3, u + 1, r[~u & 1]);
          }
        }
#pragma unroll
        for (int i = 0; i < 32; i++) xv[i] = fmaf(p1[i], G_BETA, xv[i]);
      }
    }
    asm volatile("barrier.cluster.arrive.relaxed.aligned;" ::: "memory");
    {
      const int lane = fresh_lane();
#pragma unroll
      for (int i = 0; i < 4; i++)
        stsm4(c.piece + (LMX ^ (i << 5)), pack_bf16(xv[8 * i], xv[8 * i + 1]), pack_bf16(xv[8 * i + 2], xv[8 * i + 3]),
              pack_bf16(xv[8 * i + 4], xv[8 * i + 5]), pack_bf16(xv[8 * i + 6], xv[8 * i + 7]));
    }
    fence_async_smem();
    __syncwarp();
    if (elect_one()) {
      tma_store2d(&tm_out, j * 64, g * 128 + warp * 16, c.piece);
      asm volatile("cp.async.bulk.commit_group;\ncp.async.bulk.wait_group.read 0;" ::: "memory");
    }
    __syncwarp();
    asm volatile("barrier.cluster.wait.aligned;" ::: "memory");
  }
}

typedef CUresult (*EncodeFn)(CUtensorMap*, CUtensorMapDataType, cuuint32_t, void*, const cuuint64_t*, const cuuint64_t*,
                             const cuuint32_t*, const cuuint32_t*, CUtensorMapInterleave, CUtensorMapSwizzle,
                             CUtensorMapL2promotion, CUtensorMapFloatOOBfill);

void make_map(EncodeFn enc, CUtensorMap* m, const void* ptr, int cols, int rows, int box_rows) {
  cuuint64_t gd[2] = {(cuuint64_t)cols, (cuuint64_t)rows};
  cuuint64_t gs[1] = {(cuuint64_t)cols * 2};
  cuuint32_t bx[2] = {64, (cuuint32_t)box_rows};
  cuuint32_t es[2] = {1, 1};
  enc(m, CU_TENSOR_MAP_DATA_TYPE_BFLOAT16, 2, const_cast<void*>(ptr), gd, gs, bx, es, CU_TENSOR_MAP_INTERLEAVE_NONE,
      CU_TENSOR_MAP_SWIZZLE_128B, CU_TENSOR_MAP_L2_PROMOTION_L2_256B, CU_TENSOR_MAP_FLOAT_OOB_FILL_NONE);
}

}

extern "C" void kernel_launch(void* const* d_in, const int* in_sizes, int n_in, void* d_out, int out_size) {
  (void)in_sizes; (void)n_in; (void)out_size;
  static EncodeFn enc = nullptr;
  if (!enc) {
    void* fn = nullptr;
    cudaDriverEntryPointQueryResult qr;
    cudaGetDriverEntryPoint("cuTensorMapEncodeTiled", &fn, cudaEnableDefault, &qr);
    enc = (EncodeFn)fn;
    cudaFuncSetAttribute(fused_kernel, cudaFuncAttributeMaxDynamicSharedMemorySize, SMEM_BYTES);
  }
  CUtensorMap tx, tout, twqkv, two, tw1, tw2;
  make_map(enc, &tx, d_in[0], 512, 2048, 64);
  make_map(enc, &tout, d_out, 512, 2048, 16);
  make_map(enc, &twqkv, d_in[1], 1536, 512, 64);
  make_map(enc, &two, d_in[2], 512, 512, 64);
  make_map(enc, &tw1, d_in[4], 1792, 512, 64);
  make_map(enc, &tw2, d_in[6], 512, 1792, 112);
  Params prm;
  prm.x = (const __nv_bfloat16*)d_in[0];
  prm.wqkv = (const __nv_bfloat16*)d_in[1];
  prm.wo = (const __nv_bfloat16*)d_in[2];
  prm.w1 = (const __nv_bfloat16*)d_in[4];
  prm.b1 = (const __nv_bfloat16*)d_in[5];
  prm.w2 = (const __nv_bfloat16*)d_in[6];
  prm.b2 = (const __nv_bfloat16*)d_in[7];
  for (int cl = 0; cl < 64; cl++) {
    const int pos = cl < 4 ? cl + 4 : cl < 36 ? (cl - 4) >> 3 : 4 + (cl - 36) / 7;
    const int set = cl < 4 ? 0 : cl < 36 ? (cl - 4) & 7 : 1 + (cl - 36) % 7;
    prm.role[cl] = set * 8 + pos;
  }
  fused_kernel<<<128, 384, SMEM_BYTES, cudaStreamPerThread>>>(tx, tout, twqkv, two, tw1, tw2, prm);
}
```
